```python
import torch

def _softmax(x, axis=-1):
    return torch.softmax(x, dim=axis)
def _gelu(x):
    return torch.nn.functional.gelu(x, approximate="tanh")
def _silu(x):
    return torch.nn.functional.silu(x)
def _sigmoid(x):
    return torch.sigmoid(x)
def _layernorm(x, axis=-1, eps=1e-5):
    m = x.mean(dim=axis, keepdim=True)
    v = x.var(dim=axis, keepdim=True, unbiased=False)
    return (x - m) / torch.sqrt(v + eps)
def _scatter_add(tgt, idx, src, axis=0):
    return tgt.clone().index_add_(axis, idx, src)
def _segment_sum(src, seg, n):
    out = torch.zeros((n,) + src.shape[1:], dtype=src.dtype)
    return out.index_add_(0, seg, src)
def _pad(x, pw):
    flat = tuple(v for pair in reversed(pw) for v in pair)
    return torch.nn.functional.pad(x, flat)

kernel_name = 'gated_mix__mha_block_cached__glu_gated_bilinear__decode'

def setup_inputs():

    _w = (lambda a: (lambda t: t.to(torch.bfloat16) if t.is_floating_point() else t)(torch.as_tensor(a)))
    def _A_setup():
        B, Sq, D = 1, 1, 512
        H, Sk, Dh = 32, 8192, 128
        return {
            "x": _w((lambda *s: torch.randn(*s, dtype=torch.bfloat16) * 0.05)(B, Sq, D)),
            "k_cache": _w((lambda *s: torch.randn(*s, dtype=torch.bfloat16) * 3.2)(B, H, Sk, Dh)),
            "v_cache": _w((lambda *s: torch.randn(*s, dtype=torch.bfloat16) * 0.2)(B, H, Sk, Dh)),
            "wq": _w((lambda *s: torch.randn(*s, dtype=torch.bfloat16) * 3.2)(D, H * Dh) * (D ** -0.5)),
            "wo": _w((lambda *s: torch.randn(*s, dtype=torch.bfloat16) * 0.2)(H * Dh, D) * ((H * Dh) ** -0.5)),
        }
    _A_in = _A_setup()

    def _B_setup():
        B, S, D, F = 1, 1, 512, 1376
        return {
            "x": _w((lambda *s: torch.randn(*s, dtype=torch.bfloat16) * 0.05)(B, S, D)),
            "w_gate": _w((lambda *s: torch.randn(*s, dtype=torch.bfloat16) * 0.8)(D, F) * (D ** -0.5)),
            "w_up": _w((lambda *s: torch.randn(*s, dtype=torch.bfloat16) * 0.8)(D, F) * (D ** -0.5)),
            "w_down": _w((lambda *s: torch.randn(*s, dtype=torch.bfloat16) * 0.8)(F, D) * (F ** -0.5)),
        }
    _B_in = _B_setup()

    return {
        "A_x": _A_in["x"],
        "A_k_cache": _A_in["k_cache"],
        "A_v_cache": _A_in["v_cache"],
        "A_wq": _A_in["wq"],
        "A_wo": _A_in["wo"],
        "B_x": _B_in["x"],
        "B_w_gate": _B_in["w_gate"],
        "B_w_up": _B_in["w_up"],
        "B_w_down": _B_in["w_down"],
        "gate_w": _w((lambda *s: torch.randn(*s, dtype=torch.bfloat16) * 0.1)(512) * 16.0),
    }

def reference(A_x, A_k_cache, A_v_cache, A_wq, A_wo, B_x, B_w_gate, B_w_up, B_w_down, gate_w):
    def _A_ref(x, k_cache, v_cache, wq, wo):
        B, Sq, D = x.shape
        H, Dh = 32, 128
        q = (lambda x, *d: x.permute(*d))((x @ wq).reshape(B, Sq, H, Dh), 0, 2, 1, 3)
        scores = torch.einsum("bhqd,bhkd->bhqk", q, k_cache) * (Dh ** -0.5)
        p = _softmax(scores, axis=-1)
        o = torch.einsum("bhqk,bhkd->bhqd", p, v_cache)
        return (lambda x, *d: x.permute(*d))(o, 0, 2, 1, 3).reshape(B, Sq, H * Dh) @ wo

    def _B_ref(x, w_gate, w_up, w_down):
        g = torch.einsum("bsd,df->bsf", x, w_gate)
        u = torch.einsum("bsd,df->bsf", x, w_up)
        h = g * u
        return torch.einsum("bsf,fd->bsd", h, w_down)

    x = A_x
    g = _sigmoid((x * gate_w).sum(-1, keepdims=True))
    a = _A_ref(x, A_k_cache, A_v_cache, A_wq, A_wo)
    b = _B_ref(x, B_w_gate, B_w_up, B_w_down)
    return g * a + (1 - g) * b
```

```cpp
#include <cuda_runtime.h>
#include <cuda_bf16.h>
#include <stdint.h>

namespace {

constexpr int D_MODEL = 512;
constexpr int NH      = 32;
constexpr int SK      = 8192;
constexpr int DH      = 128;
constexpr int FF      = 1376;

constexpr int NSPLIT       = 4;
constexpr int N_ATTN       = NH * NSPLIT;
constexpr int N_GLU        = 4;
constexpr int N_CTA        = N_ATTN + N_GLU;
constexpr int N_DOWN       = FF / 16;
constexpr int GU_ROWS      = 4;
constexpr int GU_PITCH     = FF * 2;
constexpr int GU_BYTES     = GU_ROWS * GU_PITCH;
constexpr int GU_TILES     = 2 * (D_MODEL / N_GLU / GU_ROWS);
constexpr int TOTAL_TILES  = N_ATTN * (2 * (SK / NSPLIT / 64) + 8) + N_DOWN;
constexpr int KEYS_PER_CTA = SK / NSPLIT;
constexpr int TILE_KEYS    = 64;
constexpr int TILE_BYTES   = TILE_KEYS * DH * 2;
constexpr int NT           = KEYS_PER_CTA / TILE_KEYS;
#define NSTAGES 12
#define MAXFLY 4
#define PACER
#define EVICT_FIRST
#define INIT_LEAD 12
#define PACE_HI 1.5f
#define PACE_LO 0.3f
#define CAP_LO 3
#define CAP_HI 5
#define GLUFLY 8

constexpr int NCW          = 8;
constexpr int NTHREADS     = (NCW + 1) * 32;
constexpr int NLAUNCH      = (NCW + 4) * 32;

constexpr int SM_RING   = 0;
constexpr int SM_P      = SM_RING + NSTAGES * TILE_BYTES;
constexpr int SM_OPART  = SM_P + NCW * 256 * 4;
constexpr int SM_QX     = SM_OPART + NCW * DH * 4;
constexpr int SM_BFRAG  = SM_QX + NSPLIT * DH * 4;
constexpr int SM_FW     = SM_BFRAG + 2 * 72 * 4;
constexpr int SM_RED    = SM_FW + 8 * 4;
constexpr int SM_PACE   = SM_RED + NCW * 4 * 4;
constexpr int SM_BARS   = SM_PACE + 16;
constexpr int SM_TOTAL  = SM_BARS + 2 * NSTAGES * 8;
constexpr int SM_GX     = SM_P;

constexpr unsigned SPIN_LIMIT = 1u << 20;

__device__ unsigned int g_progress;
__device__ unsigned int g_init;
__device__ unsigned int g_epoch;
__device__ __align__(128) uint4 g_qx[NH * NSPLIT * 64];
__device__ __align__(128) uint4 g_stats[NH * 32];
__device__ __align__(128) uint4 g_gx[N_DOWN * 64];
__device__ __align__(128) uint4 g_slots[N_ATTN * N_ATTN * 2];

__device__ __forceinline__ uint32_t smem_u32(const void* p) { return (uint32_t)__cvta_generic_to_shared(p); }
__device__ __forceinline__ void mbar_init(uint32_t bar, uint32_t cnt) {
    asm volatile("mbarrier.init.shared::cta.b64 [%0], %1;" ::"r"(bar), "r"(cnt) : "memory");
}
__device__ __forceinline__ void mbar_expect_tx(uint32_t bar, uint32_t bytes) {
    asm volatile("mbarrier.arrive.expect_tx.shared::cta.b64 _, [%0], %1;" ::"r"(bar), "r"(bytes) : "memory");
}
__device__ __forceinline__ void mbar_arrive(uint32_t bar) {
    asm volatile("mbarrier.arrive.shared::cta.b64 _, [%0];" ::"r"(bar) : "memory");
}
__device__ __forceinline__ bool mbar_try_wait(uint32_t bar, uint32_t parity) {
    uint32_t ok;
    asm volatile(
        "{\n\t.reg .pred p;\n\t"
        "mbarrier.try_wait.parity.shared::cta.b64 p, [%1], %2;\n\t"
        "selp.b32 %0, 1, 0, p;\n\t}"
        : "=r"(ok)
        : "r"(bar), "r"(parity)
        : "memory");
    return ok != 0;
}
__device__ __forceinline__ void mbar_wait(uint32_t bar, uint32_t parity) {
    unsigned n = 0;
    while (!mbar_try_wait(bar, parity)) {
        if (++n > SPIN_LIMIT) break;
    }
}
__device__ __forceinline__ void bulk_load(uint32_t dst, const void* src, uint32_t bytes, uint32_t bar) {
    asm volatile("cp.async.bulk.shared::cluster.global.mbarrier::complete_tx::bytes [%0], [%1], %2, [%3];"
                 ::"r"(dst), "l"(src), "r"(bytes), "r"(bar) : "memory");
}
__device__ __forceinline__ void bulk_load_hint(uint32_t dst, const void* src, uint32_t bytes, uint32_t bar, uint64_t pol) {
    asm volatile("cp.async.bulk.shared::cluster.global.mbarrier::complete_tx::bytes.L2::cache_hint [%0], [%1], %2, [%3], %4;"
                 ::"r"(dst), "l"(src), "r"(bytes), "r"(bar), "l"(pol) : "memory");
}
__device__ __forceinline__ uint4 ldg128(const void* p) {
    uint4 v;
    asm volatile("ld.global.nc.L1::no_allocate.v4.u32 {%0,%1,%2,%3}, [%4];"
                 : "=r"(v.x), "=r"(v.y), "=r"(v.z), "=r"(v.w) : "l"(p));
    return v;
}
__device__ __forceinline__ uint2 ldg64(const void* p) {
    uint2 v;
    asm volatile("ld.global.nc.v2.u32 {%0,%1}, [%2];" : "=r"(v.x), "=r"(v.y) : "l"(p));
    return v;
}
__device__ __forceinline__ uint4 lds128(uint32_t a) {
    uint4 v;
    asm volatile("ld.shared.v4.u32 {%0,%1,%2,%3}, [%4];" : "=r"(v.x), "=r"(v.y), "=r"(v.z), "=r"(v.w) : "r"(a));
    return v;
}
__device__ __forceinline__ void st_pkt(uint4* p, float a, float b, uint32_t tag) {
    uint64_t lo = ((uint64_t)tag << 32) | __float_as_uint(a);
    uint64_t hi = ((uint64_t)tag << 32) | __float_as_uint(b);
    asm volatile("st.relaxed.gpu.global.v2.b64 [%0], {%1, %2};" ::"l"(p), "l"(lo), "l"(hi) : "memory");
}
__device__ __forceinline__ void ld_pkt_wait(const uint4* p, uint32_t tag, float& a, float& b) {
    uint64_t lo, hi;
    unsigned n = 0;
    while (true) {
        asm volatile("ld.relaxed.gpu.global.v2.b64 {%0, %1}, [%2];" : "=l"(lo), "=l"(hi) : "l"(p) : "memory");
        if ((uint32_t)(lo >> 32) == tag && (uint32_t)(hi >> 32) == tag) break;
        if (++n > SPIN_LIMIT) break;
    }
    a = __uint_as_float((uint32_t)lo);
    b = __uint_as_float((uint32_t)hi);
}
__device__ __forceinline__ void named_bar_sync(int id, int nthreads) {
    asm volatile("bar.sync %0, %1;" ::"r"(id), "r"(nthreads) : "memory");
}
__device__ __forceinline__ float bf_lo(uint32_t w) { return __uint_as_float(w << 16); }
__device__ __forceinline__ float bf_hi(uint32_t w) { return __uint_as_float(w & 0xffff0000u); }
__device__ __forceinline__ void mma16816(float (&c)[4], uint32_t a0, uint32_t a1, uint32_t a2, uint32_t a3,
                                         uint32_t b0, uint32_t b1) {
    asm volatile(
        "mma.sync.aligned.m16n8k16.row.col.f32.bf16.bf16.f32 {%0,%1,%2,%3}, {%4,%5,%6,%7}, {%8,%9}, {%0,%1,%2,%3};"
        : "+f"(c[0]), "+f"(c[1]), "+f"(c[2]), "+f"(c[3])
        : "r"(a0), "r"(a1), "r"(a2), "r"(a3), "r"(b0), "r"(b1));
}
__device__ __forceinline__ uint32_t prmt(uint32_t a, uint32_t b, uint32_t sel) {
    uint32_t r;
    asm("prmt.b32 %0, %1, %2, %3;" : "=r"(r) : "r"(a), "r"(b), "r"(sel));
    return r;
}
__device__ __forceinline__ void to_afrag(uint4& w0, uint4& w1, uint4& w2, uint4& w3) {
#define TO_AFRAG_1(f)                                   \
    {                                                   \
        uint32_t a0 = prmt(w0.f, w1.f, 0x5410);         \
        uint32_t a1 = prmt(w0.f, w1.f, 0x7632);         \
        uint32_t a2 = prmt(w2.f, w3.f, 0x5410);         \
        uint32_t a3 = prmt(w2.f, w3.f, 0x7632);         \
        w0.f = a0; w1.f = a1; w2.f = a2; w3.f = a3;     \
    }
    TO_AFRAG_1(x) TO_AFRAG_1(y) TO_AFRAG_1(z) TO_AFRAG_1(w)
#undef TO_AFRAG_1
}
__device__ __forceinline__ float dot8(const uint4& k, const float (&q)[8]) {
    float s0 = bf_lo(k.x) * q[0];
    float s1 = bf_hi(k.x) * q[1];
    s0 = fmaf(bf_lo(k.y), q[2], s0);
    s1 = fmaf(bf_hi(k.y), q[3], s1);
    s0 = fmaf(bf_lo(k.z), q[4], s0);
    s1 = fmaf(bf_hi(k.z), q[5], s1);
    s0 = fmaf(bf_lo(k.w), q[6], s0);
    s1 = fmaf(bf_hi(k.w), q[7], s1);
    return s0 + s1;
}
__device__ __forceinline__ void axpy8(float (&acc)[8], float p, const uint4& v) {
    acc[0] = fmaf(p, bf_lo(v.x), acc[0]);
    acc[1] = fmaf(p, bf_hi(v.x), acc[1]);
    acc[2] = fmaf(p, bf_lo(v.y), acc[2]);
    acc[3] = fmaf(p, bf_hi(v.y), acc[3]);
    acc[4] = fmaf(p, bf_lo(v.z), acc[4]);
    acc[5] = fmaf(p, bf_hi(v.z), acc[5]);
    acc[6] = fmaf(p, bf_lo(v.w), acc[6]);
    acc[7] = fmaf(p, bf_hi(v.w), acc[7]);
}
__device__ __forceinline__ float warp_gate(const __nv_bfloat16* x, const __nv_bfloat16* gw, int lane) {
    uint4 xa = ldg128(x + lane * 16), xb = ldg128(x + lane * 16 + 8);
    uint4 ga = ldg128(gw + lane * 16), gb = ldg128(gw + lane * 16 + 8);
    float s = bf_lo(xa.x) * bf_lo(ga.x) + bf_hi(xa.x) * bf_hi(ga.x) + bf_lo(xa.y) * bf_lo(ga.y) + bf_hi(xa.y) * bf_hi(ga.y)
            + bf_lo(xa.z) * bf_lo(ga.z) + bf_hi(xa.z) * bf_hi(ga.z) + bf_lo(xa.w) * bf_lo(ga.w) + bf_hi(xa.w) * bf_hi(ga.w)
            + bf_lo(xb.x) * bf_lo(gb.x) + bf_hi(xb.x) * bf_hi(gb.x) + bf_lo(xb.y) * bf_lo(gb.y) + bf_hi(xb.y) * bf_hi(gb.y)
            + bf_lo(xb.z) * bf_lo(gb.z) + bf_hi(xb.z) * bf_hi(gb.z) + bf_lo(xb.w) * bf_lo(gb.w) + bf_hi(xb.w) * bf_hi(gb.w);
#pragma unroll
    for (int o = 16; o > 0; o >>= 1) s += __shfl_xor_sync(0xffffffffu, s, o);
    return 1.0f / (1.0f + __expf(-s));
}

#define PROF(i) do {} while (0)

__global__ void __launch_bounds__(NLAUNCH, 1)
fused_decode_kernel(const __nv_bfloat16* __restrict__ x, const __nv_bfloat16* __restrict__ kc,
                    const __nv_bfloat16* __restrict__ vc, const __nv_bfloat16* __restrict__ wq,
                    const __nv_bfloat16* __restrict__ wo, const __nv_bfloat16* __restrict__ w_gate,
                    const __nv_bfloat16* __restrict__ w_up, const __nv_bfloat16* __restrict__ w_down,
                    const __nv_bfloat16* __restrict__ gate_w, __nv_bfloat16* __restrict__ out) {
    extern __shared__ __align__(128) unsigned char smem[];
    const int tid = threadIdx.x, lane = tid & 31;
    const int warp = __shfl_sync(0xffffffffu, tid >> 5, 0);
    const int wg = __shfl_sync(0xffffffffu, tid >> 7, 0);
    const int b = blockIdx.x;
    const uint32_t sbase = smem_u32(smem);
    const bool is_attn = b < N_ATTN;
    const int h = b / NSPLIT, split = b % NSPLIT;
    const uint32_t bar_full = sbase + SM_BARS, bar_empty = bar_full + NSTAGES * 8;
    float* fw_s = reinterpret_cast<float*>(smem + SM_FW);
    uint32_t tag;

    if (wg == 2) {
        asm volatile("setmaxnreg.dec.sync.aligned.u32 40;");
        if (warp == NCW + 1 && is_attn) named_bar_sync(4, 64);
        if (warp == NCW + 1 && lane == 0 && is_attn) {
            volatile int* pace = reinterpret_cast<volatile int*>(smem + SM_PACE);
            const unsigned gbase = (unsigned)pace[2] * (unsigned)TOTAL_TILES;
            const int n_mine = 2 * NT + 8 + (b < N_DOWN ? 1 : 0);
            int last = 0;
            float dsum = 0.f; int dn = 0;
#pragma unroll 1
            for (unsigned n = 0; n < SPIN_LIMIT; n++) {
                const int p = pace[0];
                const int G = (int)(atomicAdd(&g_progress, (unsigned)(p - last)) + (unsigned)(p - last) - gbase);
                last = p;
                const float d = (float)(p - n_mine) - (float)G * (1.0f / N_ATTN);
                dsum += d; dn++;
                pace[1] = d > PACE_HI ? CAP_LO : (d < PACE_LO ? CAP_HI : MAXFLY);
                if (p >= n_mine) break;
            }
        }
        if (warp == NCW + 2 && is_attn) {
            asm volatile("ld.relaxed.gpu.global.u32 %0, [%1];" : "=r"(tag) : "l"(&g_epoch) : "memory");
            const float gate = warp_gate(x, gate_w, lane);
            tag += 1;
            named_bar_sync(5, NTHREADS);
            const bool dn = b < N_DOWN;
            const uint4* sp = &g_stats[h * 32 + lane];
            const uint4* gp = &g_gx[(dn ? b : 0) * 64 + (lane >> 3) * 16 + (lane & 7)];
            uint64_t v[3][2];
            unsigned n = 0;
            while (true) {
                asm volatile("ld.relaxed.gpu.global.v2.b64 {%0, %1}, [%2];" : "=l"(v[0][0]), "=l"(v[0][1]) : "l"(sp) : "memory");
                asm volatile("ld.relaxed.gpu.global.v2.b64 {%0, %1}, [%2];" : "=l"(v[1][0]), "=l"(v[1][1]) : "l"(gp) : "memory");
                asm volatile("ld.relaxed.gpu.global.v2.b64 {%0, %1}, [%2];" : "=l"(v[2][0]), "=l"(v[2][1]) : "l"(gp + 8) : "memory");
                bool ok = true;
#pragma unroll
                for (int k = 0; k < 3; k++)
                    ok = ok && (uint32_t)(v[k][0] >> 32) == tag && (uint32_t)(v[k][1] >> 32) == tag;
                if (__all_sync(0xffffffffu, ok) || ++n > SPIN_LIMIT) break;
            }
            {
                float g0 = __uint_as_float((uint32_t)v[1][0]), g1 = __uint_as_float((uint32_t)v[1][1]);
                float u0 = __uint_as_float((uint32_t)v[2][0]), u1 = __uint_as_float((uint32_t)v[2][1]);
#pragma unroll
                for (int o = 8; o <= 16; o <<= 1) {
                    g0 += __shfl_xor_sync(0xffffffffu, g0, o);
                    g1 += __shfl_xor_sync(0xffffffffu, g1, o);
                    u0 += __shfl_xor_sync(0xffffffffu, u0, o);
                    u1 += __shfl_xor_sync(0xffffffffu, u1, o);
                }
                const float h0 = dn ? g0 * u0 * (1.0f - gate) : 0.f;
                const float h1 = dn ? g1 * u1 * (1.0f - gate) : 0.f;
                if (lane < 8) {
                    uint32_t* bfrag_s = reinterpret_cast<uint32_t*>(smem + SM_BFRAG);
                    const __nv_bfloat162 hi = __floats2bfloat162_rn(h0, h1);
                    const __nv_bfloat162 lo = __floats2bfloat162_rn(h0 - __low2float(hi), h1 - __high2float(hi));
                    bfrag_s[64 + lane]      = *reinterpret_cast<const uint32_t*>(&hi);
                    bfrag_s[72 + 64 + lane] = *reinterpret_cast<const uint32_t*>(&lo);
                }
            }
            {
                const float mw = __uint_as_float((uint32_t)v[0][0]), lw = __uint_as_float((uint32_t)v[0][1]);
                float mh = mw;
#pragma unroll
                for (int o = 16; o > 0; o >>= 1) mh = fmaxf(mh, __shfl_xor_sync(0xffffffffu, mh, o));
                const float e = exp2f(mw - mh);
                float lh = lw * e;
#pragma unroll
                for (int o = 16; o > 0; o >>= 1) lh += __shfl_xor_sync(0xffffffffu, lh, o);
                if ((lane >> 3) == split) fw_s[lane & 7] = e / lh * gate;
            }
            {
                volatile int* pace = reinterpret_cast<volatile int*>(smem + SM_PACE);
                for (n = 0; pace[0] < 2 * NT + 8 - INIT_LEAD && n < SPIN_LIMIT; n++) __nanosleep(200);
#pragma unroll
                for (int k = 0; k < 8; k++) st_pkt(&g_slots[b * N_ATTN * 2 + k * 32 + lane], 0.f, 0.f, tag - 1);
                __threadfence();
                __syncwarp();
                if (lane == 0) {
                    atomicAdd(&g_init, 1u);
                    unsigned ini;
                    for (n = 0; n < SPIN_LIMIT; n++) {
                        asm volatile("ld.acquire.gpu.global.u32 %0, [%1];" : "=r"(ini) : "l"(&g_init) : "memory");
                        if ((int)(ini - tag * (unsigned)N_ATTN) >= 0) break;
                    }
                }
                __syncwarp();
            }
            named_bar_sync(1, NTHREADS);
        }
        if (warp > NCW) return;
        const size_t off = ((size_t)h * SK + (size_t)split * KEYS_PER_CTA) * DH;
        const unsigned char* ksrc = reinterpret_cast<const unsigned char*>(kc + off);
        const unsigned char* vsrc = reinterpret_cast<const unsigned char*>(vc + off);
        const int gj = b - N_ATTN;
        const unsigned char* wosrc = reinterpret_cast<const unsigned char*>(wo + (size_t)h * DH * D_MODEL);
        const int n_dn = (b < N_DOWN) ? 1 : 0;
        const int n_tiles = is_attn ? 2 * NT + 8 + n_dn : GU_TILES;
        const int max_fly = is_attn ? MAXFLY : GLUFLY;
        uint64_t pol;
        asm volatile("createpolicy.fractional.L2::evict_first.b64 %0, 1.0;" : "=l"(pol));
        auto issue = [&](int i, int s) {
            const uint32_t dst = sbase + SM_RING + s * TILE_BYTES, bar = bar_full + 8 * s;
            if (is_attn) {
                const unsigned char* src;
                if (i < 40) {
                    const int grp = i / 5, r = i - grp * 5;
                    src = (r < 4) ? ksrc + (size_t)(grp * 4 + r) * TILE_BYTES : wosrc + (size_t)grp * TILE_BYTES;
                } else if (i < 40 + n_dn) {
                    src = reinterpret_cast<const unsigned char*>(w_down + (size_t)b * 16 * D_MODEL);
                } else {
                    src = vsrc + (size_t)(i - 40 - n_dn) * TILE_BYTES;
                }
                mbar_expect_tx(bar, TILE_BYTES);
                if (i < 40 && i % 5 == 4) bulk_load(dst, src, TILE_BYTES, bar);
                else bulk_load_hint(dst, src, TILE_BYTES, bar, pol);
            } else {
                mbar_expect_tx(bar, GU_BYTES);
                bulk_load(dst, ((i & 1) ? w_up : w_gate) + (size_t)(gj * 128 + (i >> 1) * GU_ROWS) * FF, GU_BYTES, bar);
            }
        };
        if (lane == 0) {
            PROF(0);
#pragma unroll 1
            for (int s = 0; s < NSTAGES; s++) {
                mbar_init(bar_full + 8 * s, 1);
                mbar_init(bar_empty + 8 * s, NCW);
            }
            asm volatile("fence.mbarrier_init.release.cluster;" ::: "memory");
            asm volatile("fence.proxy.async.shared::cta;" ::: "memory");
#pragma unroll 1
            for (int s = 0; s < max_fly; s++) issue(s, s);
            volatile int* pace = reinterpret_cast<volatile int*>(smem + SM_PACE);
            pace[0] = max_fly;
            pace[1] = MAXFLY;
        }
        __syncwarp();
        asm volatile("ld.relaxed.gpu.global.u32 %0, [%1];" : "=r"(tag) : "l"(&g_epoch) : "memory");
        named_bar_sync(3, NTHREADS);
        tag += 1;
        if (lane == 0) reinterpret_cast<volatile int*>(smem + SM_PACE)[2] = (int)tag;
        if (is_attn) named_bar_sync(4, 64);
        if (lane == 0) {
            int s = max_fly, sf = 0, landed = 0;
            uint32_t ph = 1, phf = 0;
#pragma unroll 1
            for (int i = max_fly; i < n_tiles; i++) {
                volatile int* pace = reinterpret_cast<volatile int*>(smem + SM_PACE);
                const int lag = is_attn ? pace[1] : GLUFLY;
                while (landed <= i - lag) {
                    mbar_wait(bar_full + 8 * sf, phf);
                    if (++sf == NSTAGES) { sf = 0; phf ^= 1; }
                    landed++;
                }
                mbar_wait(bar_empty + 8 * s, ph);
                issue(i, s);
                pace[0] = i + 1;
                if (++s == NSTAGES) { s = 0; ph ^= 1; }
            }
        }
        return;
    }

    asm volatile("setmaxnreg.inc.sync.aligned.u32 232;");
    int s = 0;
    uint32_t ph = 0;
    auto advance = [&]() {
        __syncwarp();
        if (lane == 0) mbar_arrive(bar_empty + 8 * s);
        if (++s == NSTAGES) { s = 0; ph ^= 1; }
    };

    if (!is_attn) {
        float* x_s = reinterpret_cast<float*>(smem + SM_GX);
        {
            const uint32_t xx = *reinterpret_cast<const uint32_t*>(x + 2 * tid);
            asm volatile("ld.relaxed.gpu.global.u32 %0, [%1];" : "=r"(tag) : "l"(&g_epoch) : "memory");
            *reinterpret_cast<float2*>(x_s + 2 * tid) = make_float2(bf_lo(xx), bf_hi(xx));
        }
        named_bar_sync(3, NTHREADS);
        tag += 1;
        const int gj = b - N_ATTN;
        {
            const bool act = tid < 172;
            const uint32_t off = act ? tid * 16 : 0;
            float ag[8], au[8];
#pragma unroll
            for (int j = 0; j < 8; j++) ag[j] = au[j] = 0.f;
#pragma unroll 1
            for (int it = 0; it < GU_TILES / 2; it++) {
                const float4 p = *reinterpret_cast<const float4*>(x_s + gj * 128 + it * GU_ROWS);
                {
                    mbar_wait(bar_full + 8 * s, ph);
                    const uint32_t a = sbase + SM_RING + s * TILE_BYTES + off;
                    const uint4 v0 = lds128(a), v1 = lds128(a + GU_PITCH), v2 = lds128(a + 2 * GU_PITCH),
                                v3 = lds128(a + 3 * GU_PITCH);
                    axpy8(ag, p.x, v0); axpy8(ag, p.y, v1); axpy8(ag, p.z, v2); axpy8(ag, p.w, v3);
                    advance();
                }
                {
                    mbar_wait(bar_full + 8 * s, ph);
                    const uint32_t a = sbase + SM_RING + s * TILE_BYTES + off;
                    const uint4 v0 = lds128(a), v1 = lds128(a + GU_PITCH), v2 = lds128(a + 2 * GU_PITCH),
                                v3 = lds128(a + 3 * GU_PITCH);
                    axpy8(au, p.x, v0); axpy8(au, p.y, v1); axpy8(au, p.z, v2); axpy8(au, p.w, v3);
                    advance();
                }
            }
            if (act) {
                uint4* gp = &g_gx[(tid >> 1) * 64 + gj * 16 + (tid & 1) * 4];
#pragma unroll
                for (int k = 0; k < 4; k++) {
                    st_pkt(gp + k, ag[2 * k], ag[2 * k + 1], tag);
                    st_pkt(gp + 8 + k, au[2 * k], au[2 * k + 1], tag);
                }
            }
        }
        if (tid == 0) PROF(5);
        return;
    }

    const int g = lane >> 2, t = lane & 3;
    float* opart_s = reinterpret_cast<float*>(smem + SM_OPART);
    uint32_t* bfrag_s = reinterpret_cast<uint32_t*>(smem + SM_BFRAG);
    float q[8];
    {
        const int row0 = split * 128 + warp * 16;
        const __nv_bfloat16* wp = wq + (size_t)(row0 + (lane >> 4)) * (NH * DH) + h * DH + (lane & 15) * 8;
        uint4 wv[8];
#pragma unroll
        for (int i = 0; i < 8; i++) wv[i] = ldg128(wp + (size_t)(2 * i) * (NH * DH));
        const uint4 xa = ldg128(x + row0), xb = ldg128(x + row0 + 8);
        asm volatile("ld.relaxed.gpu.global.u32 %0, [%1];" : "=r"(tag) : "l"(&g_epoch) : "memory");
        named_bar_sync(3, NTHREADS);
        const uint32_t xw[8] = {xa.x, xa.y, xa.z, xa.w, xb.x, xb.y, xb.z, xb.w};
        float acc[8];
#pragma unroll
        for (int j = 0; j < 8; j++) acc[j] = 0.f;
#pragma unroll
        for (int i = 0; i < 8; i++) axpy8(acc, lane >= 16 ? bf_hi(xw[i]) : bf_lo(xw[i]), wv[i]);
#pragma unroll
        for (int j = 0; j < 8; j++) acc[j] += __shfl_xor_sync(0xffffffffu, acc[j], 16);
        float* op = opart_s + warp * DH + (lane & 15) * 8 + (lane >> 4) * 4;
        *reinterpret_cast<float4*>(op) = lane >= 16 ? make_float4(acc[4], acc[5], acc[6], acc[7])
                                                    : make_float4(acc[0], acc[1], acc[2], acc[3]);
        tag += 1;
        named_bar_sync(2, NCW * 32);
        if (tid < 64) {
            float q0 = 0.f, q1 = 0.f;
#pragma unroll
            for (int ww = 0; ww < NCW; ww++) {
                const float2 v = *reinterpret_cast<const float2*>(opart_s + ww * DH + 2 * tid);
                q0 += v.x;
                q1 += v.y;
            }
            st_pkt(&g_qx[b * 64 + tid], q0, q1, tag);
        }
        if (tid == 0) PROF(6);
        float q0, q1;
        ld_pkt_wait(&g_qx[h * NSPLIT * 64 + tid], tag, q0, q1);
        float* qs = reinterpret_cast<float*>(smem + SM_QX);
        *reinterpret_cast<float2*>(qs + 2 * tid) = make_float2(q0, q1);
        named_bar_sync(2, NCW * 32);
        const float sc = 0.08838834764831845f * 1.4426950408889634f;
#pragma unroll
        for (int j = 0; j < 8; j++) q[j] = 0.f;
#pragma unroll
        for (int sp = 0; sp < NSPLIT; sp++) {
            const float4 a = *reinterpret_cast<const float4*>(qs + sp * DH + (lane & 15) * 8);
            const float4 c = *reinterpret_cast<const float4*>(qs + sp * DH + (lane & 15) * 8 + 4);
            q[0] += a.x; q[1] += a.y; q[2] += a.z; q[3] += a.w;
            q[4] += c.x; q[5] += c.y; q[6] += c.z; q[7] += c.w;
        }
#pragma unroll
        for (int j = 0; j < 8; j++) q[j] *= sc;
    }
    if (tid == 0) PROF(1);

    uint4 w[36];
    const uint32_t wf_off = (4 * t) * 1024 + warp * 128 + g * 16;
    const uint32_t my_off = warp * 2048 + lane * 16;
    float* p_s = reinterpret_cast<float*>(smem + SM_P) + warp * 256;
#pragma unroll
    for (int grp = 0; grp < 8; grp++) {
#pragma unroll 1
        for (int r = 0; r < 4; r++) {
            mbar_wait(bar_full + 8 * s, ph);
            const uint32_t a = sbase + SM_RING + s * TILE_BYTES + my_off;
            const uint4 k0 = lds128(a), k1 = lds128(a + 512), k2 = lds128(a + 1024), k3 = lds128(a + 1536);
            float s0 = dot8(k0, q), s1 = dot8(k1, q), s2 = dot8(k2, q), s3 = dot8(k3, q);
            advance();
            const bool b3 = lane & 8, b2 = lane & 4;
            float u0 = b3 ? s2 : s0, u1 = b3 ? s3 : s1;
            float v0 = b3 ? s0 : s2, v1 = b3 ? s1 : s3;
            u0 += __shfl_xor_sync(0xffffffffu, v0, 8);
            u1 += __shfl_xor_sync(0xffffffffu, v1, 8);
            float rr = b2 ? u1 : u0, r2 = b2 ? u0 : u1;
            rr += __shfl_xor_sync(0xffffffffu, r2, 4);
            rr += __shfl_xor_sync(0xffffffffu, rr, 2);
            rr += __shfl_xor_sync(0xffffffffu, rr, 1);
            if ((lane & 3) == 0) p_s[(grp * 4 + r) * 8 + (lane >> 2)] = rr;
        }
        {
            mbar_wait(bar_full + 8 * s, ph);
            const uint32_t a = sbase + SM_RING + s * TILE_BYTES + wf_off;
            w[grp * 4] = lds128(a); w[grp * 4 + 1] = lds128(a + 1024);
            w[grp * 4 + 2] = lds128(a + 2048); w[grp * 4 + 3] = lds128(a + 3072);
            to_afrag(w[grp * 4], w[grp * 4 + 1], w[grp * 4 + 2], w[grp * 4 + 3]);
            advance();
        }
    }
    if (b < N_DOWN) {
        mbar_wait(bar_full + 8 * s, ph);
        const uint32_t a = sbase + SM_RING + s * TILE_BYTES + wf_off;
        w[32] = lds128(a); w[33] = lds128(a + 1024); w[34] = lds128(a + 2048); w[35] = lds128(a + 3072);
        to_afrag(w[32], w[33], w[34], w[35]);
        advance();
    } else {
        w[32] = w[33] = w[34] = w[35] = make_uint4(0, 0, 0, 0);
    }
    __syncwarp();
    if (tid == 0) PROF(2);
    {
        float4 sa = *reinterpret_cast<float4*>(p_s + lane * 8);
        float4 sb = *reinterpret_cast<float4*>(p_s + lane * 8 + 4);
        float m = fmaxf(fmaxf(fmaxf(sa.x, sa.y), fmaxf(sa.z, sa.w)), fmaxf(fmaxf(sb.x, sb.y), fmaxf(sb.z, sb.w)));
#pragma unroll
        for (int o = 16; o > 0; o >>= 1) m = fmaxf(m, __shfl_xor_sync(0xffffffffu, m, o));
        sa.x = exp2f(sa.x - m); sa.y = exp2f(sa.y - m); sa.z = exp2f(sa.z - m); sa.w = exp2f(sa.w - m);
        sb.x = exp2f(sb.x - m); sb.y = exp2f(sb.y - m); sb.z = exp2f(sb.z - m); sb.w = exp2f(sb.w - m);
        float l = ((sa.x + sa.y) + (sa.z + sa.w)) + ((sb.x + sb.y) + (sb.z + sb.w));
#pragma unroll
        for (int o = 16; o > 0; o >>= 1) l += __shfl_xor_sync(0xffffffffu, l, o);
        *reinterpret_cast<float4*>(p_s + lane * 8) = sa;
        *reinterpret_cast<float4*>(p_s + lane * 8 + 4) = sb;
        if (lane == 0) st_pkt(&g_stats[h * 32 + split * 8 + warp], m, l, tag);
        asm volatile("bar.arrive 5, %0;" ::"r"(NTHREADS) : "memory");
        __syncwarp();
    }
    float acc[8];
#pragma unroll
    for (int j = 0; j < 8; j++) acc[j] = 0.f;
    const float* p_rd = p_s + (lane >> 4) * 4;
#pragma unroll 1
    for (int it = 0; it < NT; it++) {
        const float4 p = *reinterpret_cast<const float4*>(p_rd + it * 8);
        mbar_wait(bar_full + 8 * s, ph);
        const uint32_t a = sbase + SM_RING + s * TILE_BYTES + my_off;
        const uint4 v0 = lds128(a), v1 = lds128(a + 512), v2 = lds128(a + 1024), v3 = lds128(a + 1536);
        axpy8(acc, p.x, v0);
        axpy8(acc, p.y, v1);
        axpy8(acc, p.z, v2);
        axpy8(acc, p.w, v3);
        advance();
    }
    if (tid == 0) PROF(3);
#pragma unroll
    for (int j = 0; j < 8; j++) acc[j] += __shfl_xor_sync(0xffffffffu, acc[j], 16);
    {
        float* op = opart_s + warp * DH + (lane & 15) * 8 + (lane >> 4) * 4;
        *reinterpret_cast<float4*>(op) = lane >= 16 ? make_float4(acc[4], acc[5], acc[6], acc[7])
                                                    : make_float4(acc[0], acc[1], acc[2], acc[3]);
    }
    named_bar_sync(1, NTHREADS);
    if (tid < 64) {
        const float* op = opart_s + 2 * tid;
        const float4 fa = *reinterpret_cast<const float4*>(fw_s), fb = *reinterpret_cast<const float4*>(fw_s + 4);
        const float f[8] = {fa.x, fa.y, fa.z, fa.w, fb.x, fb.y, fb.z, fb.w};
        float o0 = 0.f, o1 = 0.f;
#pragma unroll
        for (int ww = 0; ww < NCW; ww++) {
            const float2 v = *reinterpret_cast<const float2*>(op + ww * DH);
            o0 = fmaf(f[ww], v.x, o0);
            o1 = fmaf(f[ww], v.y, o1);
        }
        const __nv_bfloat162 hi = __floats2bfloat162_rn(o0, o1);
        const __nv_bfloat162 lo = __floats2bfloat162_rn(o0 - __low2float(hi), o1 - __high2float(hi));
        bfrag_s[tid]      = *reinterpret_cast<const uint32_t*>(&hi);
        bfrag_s[72 + tid] = *reinterpret_cast<const uint32_t*>(&lo);
    }
    named_bar_sync(2, NCW * 32);
    {
        const uint32_t* bf = bfrag_s + (g & 1) * 72 + 2 * t;
        float c[2][4][4];
#pragma unroll
        for (int u = 0; u < 2; u++)
#pragma unroll
            for (int j = 0; j < 4; j++) c[u][j][0] = c[u][j][1] = c[u][j][2] = c[u][j][3] = 0.f;
#pragma unroll
        for (int ks = 0; ks < 9; ks++) {
            const uint2 bb = *reinterpret_cast<const uint2*>(bf + 8 * ks);
            mma16816(c[ks & 1][0], w[ks * 4].x, w[ks * 4 + 1].x, w[ks * 4 + 2].x, w[ks * 4 + 3].x, bb.x, bb.y);
            mma16816(c[ks & 1][1], w[ks * 4].y, w[ks * 4 + 1].y, w[ks * 4 + 2].y, w[ks * 4 + 3].y, bb.x, bb.y);
            mma16816(c[ks & 1][2], w[ks * 4].z, w[ks * 4 + 1].z, w[ks * 4 + 2].z, w[ks * 4 + 3].z, bb.x, bb.y);
            mma16816(c[ks & 1][3], w[ks * 4].w, w[ks * 4 + 1].w, w[ks * 4 + 2].w, w[ks * 4 + 3].w, bb.x, bb.y);
        }
        float ya[4], yb[4];
#pragma unroll
        for (int j = 0; j < 4; j++) {
            ya[j] = (c[0][j][0] + c[1][j][0]) + (c[0][j][1] + c[1][j][1]);
            yb[j] = (c[0][j][2] + c[1][j][2]) + (c[0][j][3] + c[1][j][3]);
        }
        const float y0 = t == 0 ? ya[0] : t == 1 ? ya[1] : t == 2 ? ya[2] : ya[3];
        const float y1 = t == 0 ? yb[0] : t == 1 ? yb[1] : t == 2 ? yb[2] : yb[3];
        st_pkt(&g_slots[((tid >> 1) * N_ATTN + b) * 2 + (tid & 1)], y0, y1, tag);
    }
    if (tid == 0) PROF(4);
    if (warp < 2) {
        const uint4* sp = &g_slots[(b * N_ATTN + lane) * 2 + warp];
        float a0, a1;
        unsigned n = 0;
        while (true) {
            uint64_t v[4][2];
#pragma unroll
            for (int k = 0; k < 4; k++)
                asm volatile("ld.relaxed.gpu.global.v2.b64 {%0, %1}, [%2];"
                             : "=l"(v[k][0]), "=l"(v[k][1]) : "l"(sp + 64 * k) : "memory");
            bool ok = true;
            a0 = a1 = 0.f;
#pragma unroll
            for (int k = 0; k < 4; k++) {
                ok = ok && (uint32_t)(v[k][0] >> 32) == tag && (uint32_t)(v[k][1] >> 32) == tag;
                a0 += __uint_as_float((uint32_t)v[k][0]);
                a1 += __uint_as_float((uint32_t)v[k][1]);
            }
            if (ok || ++n > SPIN_LIMIT) break;
        }
        __syncwarp();
#pragma unroll
        for (int o = 16; o > 0; o >>= 1) {
            a0 += __shfl_xor_sync(0xffffffffu, a0, o);
            a1 += __shfl_xor_sync(0xffffffffu, a1, o);
        }
        if (lane == 0) {
            *reinterpret_cast<__nv_bfloat162*>(out + 4 * b + 2 * warp) = __floats2bfloat162_rn(a0, a1);
            if (b == 0 && warp == 0) g_epoch = tag;
            if (tid == 0) PROF(5);
        }
    }
}

}

extern "C" void kernel_launch(void* const* d_in, const int* in_sizes, int n_in, void* d_out, int out_size) {
    (void)in_sizes; (void)n_in; (void)out_size;
    const __nv_bfloat16* x      = (const __nv_bfloat16*)d_in[0];
    const __nv_bfloat16* kc     = (const __nv_bfloat16*)d_in[1];
    const __nv_bfloat16* vc     = (const __nv_bfloat16*)d_in[2];
    const __nv_bfloat16* wq     = (const __nv_bfloat16*)d_in[3];
    const __nv_bfloat16* wo     = (const __nv_bfloat16*)d_in[4];
    const __nv_bfloat16* w_gate = (const __nv_bfloat16*)d_in[6];
    const __nv_bfloat16* w_up   = (const __nv_bfloat16*)d_in[7];
    const __nv_bfloat16* w_down = (const __nv_bfloat16*)d_in[8];
    const __nv_bfloat16* gate_w = (const __nv_bfloat16*)d_in[9];

    cudaFuncSetAttribute(fused_decode_kernel, cudaFuncAttributeMaxDynamicSharedMemorySize, SM_TOTAL);
    fused_decode_kernel<<<N_CTA, NLAUNCH, SM_TOTAL>>>(x, kc, vc, wq, wo, w_gate, w_up, w_down, gate_w,
                                                     (__nv_bfloat16*)d_out);
}
```

```cpp
#include <cuda_runtime.h>
#include <cuda_bf16.h>
#include <stdint.h>

namespace {

constexpr int D_MODEL = 512;
constexpr int NH      = 32;
constexpr int SK      = 8192;
constexpr int DH      = 128;
constexpr int FF      = 1376;

constexpr int NSPLIT       = 4;
constexpr int N_ATTN       = NH * NSPLIT;
constexpr int N_GLU        = 4;
constexpr int N_CTA        = N_ATTN + N_GLU;
constexpr int N_DOWN       = FF / 16;
constexpr int GU_ROWS      = 4;
constexpr int GU_PITCH     = FF * 2;
constexpr int GU_BYTES     = GU_ROWS * GU_PITCH;
constexpr int GU_TILES     = 2 * (D_MODEL / N_GLU / GU_ROWS);
constexpr int TOTAL_TILES  = N_ATTN * (2 * (SK / NSPLIT / 64) + 8) + N_DOWN;
constexpr int KEYS_PER_CTA = SK / NSPLIT;
constexpr int TILE_KEYS    = 64;
constexpr int TILE_BYTES   = TILE_KEYS * DH * 2;
constexpr int NT           = KEYS_PER_CTA / TILE_KEYS;
#define NSTAGES 12
#define MAXFLY 4
#define CAP_LO 2
#define CAP_HI 6
#define PACE_K 1.5f
#define PACE_D0 0.6f
#define GLUFLY 8
#define TAIL_LEAD 12

constexpr int NCW          = 8;
constexpr int NLAUNCH      = (NCW + 4) * 32;
constexpr int BAR_SCALE = 1;
constexpr int BAR_CONS  = 2;
constexpr int BAR_INIT  = 3;
constexpr int BAR_KDONE = 5;

constexpr int SM_RING   = 0;
constexpr int SM_P      = SM_RING + NSTAGES * TILE_BYTES;
constexpr int SM_OPART  = SM_P + NCW * 256 * 4;
constexpr int SM_QX     = SM_OPART + NCW * DH * 4;
constexpr int SM_BFRAG  = SM_QX + NSPLIT * DH * 4;
constexpr int SM_FW     = SM_BFRAG + 8 * 72 * 4;
constexpr int SM_PACE   = SM_FW + 8 * 4;
constexpr int SM_BARS   = SM_PACE + 16;
constexpr int SM_TOTAL  = SM_BARS + 2 * NSTAGES * 8;
constexpr int SM_GX     = SM_P;

constexpr unsigned SPIN_LIMIT = 1u << 20;

__device__ unsigned int g_epoch;
__device__ unsigned int g_progress[2];
__device__ __align__(128) uint4 g_qx[NH * NSPLIT * 64];
__device__ __align__(128) uint4 g_stats[NH * 32];
__device__ __align__(128) uint4 g_gx[N_DOWN * 64];
__device__ __align__(128) uint4 g_slots[N_ATTN * N_ATTN * 2];

__device__ __forceinline__ uint32_t smem_u32(const void* p) { return (uint32_t)__cvta_generic_to_shared(p); }
__device__ __forceinline__ void mbar_init(uint32_t bar, uint32_t cnt) {
    asm volatile("mbarrier.init.shared::cta.b64 [%0], %1;" ::"r"(bar), "r"(cnt) : "memory");
}
__device__ __forceinline__ void mbar_expect_tx(uint32_t bar, uint32_t bytes) {
    asm volatile("mbarrier.arrive.expect_tx.shared::cta.b64 _, [%0], %1;" ::"r"(bar), "r"(bytes) : "memory");
}
__device__ __forceinline__ void mbar_arrive(uint32_t bar) {
    asm volatile("mbarrier.arrive.shared::cta.b64 _, [%0];" ::"r"(bar) : "memory");
}
__device__ __forceinline__ bool mbar_try_wait(uint32_t bar, uint32_t parity) {
    uint32_t ok;
    asm volatile(
        "{\n\t.reg .pred p;\n\t"
        "mbarrier.try_wait.parity.shared::cta.b64 p, [%1], %2;\n\t"
        "selp.b32 %0, 1, 0, p;\n\t}"
        : "=r"(ok)
        : "r"(bar), "r"(parity)
        : "memory");
    return ok != 0;
}
__device__ __forceinline__ void mbar_wait(uint32_t bar, uint32_t parity) {
    unsigned n = 0;
    while (!mbar_try_wait(bar, parity)) {
        if (++n > SPIN_LIMIT) break;
    }
}
__device__ __forceinline__ void bulk_load(uint32_t dst, const void* src, uint32_t bytes, uint32_t bar) {
    asm volatile("cp.async.bulk.shared::cluster.global.mbarrier::complete_tx::bytes [%0], [%1], %2, [%3];"
                 ::"r"(dst), "l"(src), "r"(bytes), "r"(bar) : "memory");
}
__device__ __forceinline__ void bulk_load_hint(uint32_t dst, const void* src, uint32_t bytes, uint32_t bar, uint64_t pol) {
    asm volatile("cp.async.bulk.shared::cluster.global.mbarrier::complete_tx::bytes.L2::cache_hint [%0], [%1], %2, [%3], %4;"
                 ::"r"(dst), "l"(src), "r"(bytes), "r"(bar), "l"(pol) : "memory");
}
__device__ __forceinline__ uint4 ldg128(const void* p) {
    uint4 v;
    asm volatile("ld.global.nc.L1::no_allocate.v4.u32 {%0,%1,%2,%3}, [%4];"
                 : "=r"(v.x), "=r"(v.y), "=r"(v.z), "=r"(v.w) : "l"(p));
    return v;
}
__device__ __forceinline__ uint2 ldg64(const void* p) {
    uint2 v;
    asm volatile("ld.global.nc.v2.u32 {%0,%1}, [%2];" : "=r"(v.x), "=r"(v.y) : "l"(p));
    return v;
}
__device__ __forceinline__ uint4 lds128(uint32_t a) {
    uint4 v;
    asm volatile("ld.shared.v4.u32 {%0,%1,%2,%3}, [%4];" : "=r"(v.x), "=r"(v.y), "=r"(v.z), "=r"(v.w) : "r"(a));
    return v;
}
__device__ __forceinline__ void st_pkt(uint4* p, float a, float b, uint32_t tag) {
    uint64_t lo = ((uint64_t)tag << 32) | __float_as_uint(a);
    uint64_t hi = ((uint64_t)tag << 32) | __float_as_uint(b);
    asm volatile("st.relaxed.gpu.global.v2.b64 [%0], {%1, %2};" ::"l"(p), "l"(lo), "l"(hi) : "memory");
}
__device__ __forceinline__ void ld_pkt_wait(const uint4* p, uint32_t tag, float& a, float& b) {
    uint64_t lo, hi;
    unsigned n = 0;
    while (true) {
        asm volatile("ld.relaxed.gpu.global.v2.b64 {%0, %1}, [%2];" : "=l"(lo), "=l"(hi) : "l"(p) : "memory");
        if ((uint32_t)(lo >> 32) == tag && (uint32_t)(hi >> 32) == tag) break;
        if (++n > SPIN_LIMIT) break;
    }
    a = __uint_as_float((uint32_t)lo);
    b = __uint_as_float((uint32_t)hi);
}
__device__ __forceinline__ void named_bar_sync(int id, int nthreads) {
    asm volatile("bar.sync %0, %1;" ::"r"(id), "r"(nthreads) : "memory");
}
__device__ __forceinline__ void named_bar_arrive(int id, int nthreads) {
    asm volatile("bar.arrive %0, %1;" ::"r"(id), "r"(nthreads) : "memory");
}
__device__ __forceinline__ float bf_lo(uint32_t w) { return __uint_as_float(w << 16); }
__device__ __forceinline__ float bf_hi(uint32_t w) { return __uint_as_float(w & 0xffff0000u); }
__device__ __forceinline__ void mma16816(float (&c)[4], uint32_t a0, uint32_t a1, uint32_t a2, uint32_t a3,
                                         uint32_t b0, uint32_t b1) {
    asm volatile(
        "mma.sync.aligned.m16n8k16.row.col.f32.bf16.bf16.f32 {%0,%1,%2,%3}, {%4,%5,%6,%7}, {%8,%9}, {%0,%1,%2,%3};"
        : "+f"(c[0]), "+f"(c[1]), "+f"(c[2]), "+f"(c[3])
        : "r"(a0), "r"(a1), "r"(a2), "r"(a3), "r"(b0), "r"(b1));
}
__device__ __forceinline__ uint32_t prmt(uint32_t a, uint32_t b, uint32_t sel) {
    uint32_t r;
    asm("prmt.b32 %0, %1, %2, %3;" : "=r"(r) : "r"(a), "r"(b), "r"(sel));
    return r;
}
__device__ __forceinline__ void to_afrag(uint4& w0, uint4& w1, uint4& w2, uint4& w3) {
#define TO_AFRAG_1(f)                                   \
    {                                                   \
        uint32_t a0 = prmt(w0.f, w1.f, 0x5410);         \
        uint32_t a1 = prmt(w0.f, w1.f, 0x7632);         \
        uint32_t a2 = prmt(w2.f, w3.f, 0x5410);         \
        uint32_t a3 = prmt(w2.f, w3.f, 0x7632);         \
        w0.f = a0; w1.f = a1; w2.f = a2; w3.f = a3;     \
    }
    TO_AFRAG_1(x) TO_AFRAG_1(y) TO_AFRAG_1(z) TO_AFRAG_1(w)
#undef TO_AFRAG_1
}
__device__ __forceinline__ float dot8(const uint4& k, const float (&q)[8]) {
    float s0 = bf_lo(k.x) * q[0];
    float s1 = bf_hi(k.x) * q[1];
    s0 = fmaf(bf_lo(k.y), q[2], s0);
    s1 = fmaf(bf_hi(k.y), q[3], s1);
    s0 = fmaf(bf_lo(k.z), q[4], s0);
    s1 = fmaf(bf_hi(k.z), q[5], s1);
    s0 = fmaf(bf_lo(k.w), q[6], s0);
    s1 = fmaf(bf_hi(k.w), q[7], s1);
    return s0 + s1;
}
__device__ __forceinline__ void axpy8(float (&acc)[8], float p, const uint4& v) {
    acc[0] = fmaf(p, bf_lo(v.x), acc[0]);
    acc[1] = fmaf(p, bf_hi(v.x), acc[1]);
    acc[2] = fmaf(p, bf_lo(v.y), acc[2]);
    acc[3] = fmaf(p, bf_hi(v.y), acc[3]);
    acc[4] = fmaf(p, bf_lo(v.z), acc[4]);
    acc[5] = fmaf(p, bf_hi(v.z), acc[5]);
    acc[6] = fmaf(p, bf_lo(v.w), acc[6]);
    acc[7] = fmaf(p, bf_hi(v.w), acc[7]);
}
__device__ __forceinline__ float warp_gate(const __nv_bfloat16* x, const __nv_bfloat16* gw, int lane) {
    uint4 xa = ldg128(x + lane * 16), xb = ldg128(x + lane * 16 + 8);
    uint4 ga = ldg128(gw + lane * 16), gb = ldg128(gw + lane * 16 + 8);
    float s = bf_lo(xa.x) * bf_lo(ga.x) + bf_hi(xa.x) * bf_hi(ga.x) + bf_lo(xa.y) * bf_lo(ga.y) + bf_hi(xa.y) * bf_hi(ga.y)
            + bf_lo(xa.z) * bf_lo(ga.z) + bf_hi(xa.z) * bf_hi(ga.z) + bf_lo(xa.w) * bf_lo(ga.w) + bf_hi(xa.w) * bf_hi(ga.w)
            + bf_lo(xb.x) * bf_lo(gb.x) + bf_hi(xb.x) * bf_hi(gb.x) + bf_lo(xb.y) * bf_lo(gb.y) + bf_hi(xb.y) * bf_hi(gb.y)
            + bf_lo(xb.z) * bf_lo(gb.z) + bf_hi(xb.z) * bf_hi(gb.z) + bf_lo(xb.w) * bf_lo(gb.w) + bf_hi(xb.w) * bf_hi(gb.w);
#pragma unroll
    for (int o = 16; o > 0; o >>= 1) s += __shfl_xor_sync(0xffffffffu, s, o);
    return 1.0f / (1.0f + __expf(-s));
}

#define CLK(i) do {} while (0)
#define PROF(i) do {} while (0)

__global__ void __launch_bounds__(NLAUNCH, 1)
fused_decode_kernel(const __nv_bfloat16* __restrict__ x, const __nv_bfloat16* __restrict__ kc,
                    const __nv_bfloat16* __restrict__ vc, const __nv_bfloat16* __restrict__ wq,
                    const __nv_bfloat16* __restrict__ wo, const __nv_bfloat16* __restrict__ w_gate,
                    const __nv_bfloat16* __restrict__ w_up, const __nv_bfloat16* __restrict__ w_down,
                    const __nv_bfloat16* __restrict__ gate_w, __nv_bfloat16* __restrict__ out) {
    extern __shared__ __align__(128) unsigned char smem[];
    const int tid = threadIdx.x, lane = tid & 31;
    const int warp = __shfl_sync(0xffffffffu, tid >> 5, 0);
    const int wg = __shfl_sync(0xffffffffu, tid >> 7, 0);
    const int b = blockIdx.x;
    const uint32_t sbase = smem_u32(smem);
    const bool is_attn = b < N_ATTN;
    const int h = b / NSPLIT, split = b % NSPLIT;
    const uint32_t bar_full = sbase + SM_BARS, bar_empty = bar_full + NSTAGES * 8;
    float* fw_s = reinterpret_cast<float*>(smem + SM_FW);
    uint32_t tag;

    if (wg == 2) {
        asm volatile("setmaxnreg.dec.sync.aligned.u32 40;");
        volatile int* pace = reinterpret_cast<volatile int*>(smem + SM_PACE);
        const int n_dn = (b < N_DOWN) ? 1 : 0;
        const int n_tiles = is_attn ? 2 * NT + 8 + n_dn : GU_TILES;
        if (warp == NCW) {
            const size_t off = (size_t)b * KEYS_PER_CTA * DH;
            const unsigned char* ksrc = reinterpret_cast<const unsigned char*>(kc + off);
            const unsigned char* vsrc = reinterpret_cast<const unsigned char*>(vc + off);
            const unsigned char* wosrc = reinterpret_cast<const unsigned char*>(wo + (size_t)h * DH * D_MODEL);
            const int gj = b - N_ATTN;
            const int max_fly = is_attn ? MAXFLY : GLUFLY;
            uint64_t pol;
            asm volatile("createpolicy.fractional.L2::evict_first.b64 %0, 1.0;" : "=l"(pol));
            auto issue = [&](int i, int s) {
                const uint32_t dst = sbase + SM_RING + s * TILE_BYTES, bar = bar_full + 8 * s;
                if (is_attn) {
                    mbar_expect_tx(bar, TILE_BYTES);
                    if (i < 40) {
                        const int grp = i / 5, r = i - grp * 5;
                        if (r < 4) bulk_load_hint(dst, ksrc + (size_t)(grp * 4 + r) * TILE_BYTES, TILE_BYTES, bar, pol);
                        else       bulk_load(dst, wosrc + (size_t)grp * TILE_BYTES, TILE_BYTES, bar);
                    } else {
                        const unsigned char* src =
                            (i < 40 + n_dn) ? reinterpret_cast<const unsigned char*>(w_down + (size_t)b * 16 * D_MODEL)
                                            : vsrc + (size_t)(i - 40 - n_dn) * TILE_BYTES;
                        bulk_load_hint(dst, src, TILE_BYTES, bar, pol);
                    }
                } else {
                    mbar_expect_tx(bar, GU_BYTES);
                    bulk_load_hint(dst, ((i & 1) ? w_up : w_gate) + (size_t)(gj * 128 + (i >> 1) * GU_ROWS) * FF,
                                   GU_BYTES, bar, pol);
                }
            };
            if (lane == 0) {
                PROF(0);
#pragma unroll
                for (int s = 0; s < NSTAGES; s++) mbar_init(bar_full + 8 * s, 1);
                asm volatile("fence.mbarrier_init.release.cluster;" ::: "memory");
                asm volatile("fence.proxy.async.shared::cta;" ::: "memory");
#pragma unroll 1
                for (int s = 0; s < max_fly; s++) issue(s, s);
#pragma unroll
                for (int s = 0; s < NSTAGES; s++) mbar_init(bar_empty + 8 * s, NCW);
                pace[0] = max_fly;
                pace[1] = max_fly;
            }
            __syncwarp();
            named_bar_arrive(BAR_INIT, 320);
            if (lane == 0) {
                int s = max_fly, sf = 0, landed = 0;
                uint32_t ph = 1, phf = 0;
#pragma unroll 1
                for (int i = max_fly; i < n_tiles; i++) {
                    const int lag = pace[1];
                    while (landed <= i - lag) {
                        mbar_wait(bar_full + 8 * sf, phf);
                        if (++sf == NSTAGES) { sf = 0; phf ^= 1; }
                        landed++;
                    }
                    mbar_wait(bar_empty + 8 * s, ph);
                    issue(i, s);
                    pace[0] = i + 1;
                    if (++s == NSTAGES) { s = 0; ph ^= 1; }
                }
            }
            return;
        }
        if (warp == NCW + 1) {
            asm volatile("ld.relaxed.gpu.global.u32 %0, [%1];" : "=r"(tag) : "l"(&g_epoch) : "memory");
            named_bar_sync(BAR_INIT, 320);
            if (lane == 0 && is_attn) {
                unsigned* ctr = &g_progress[tag & 1];
                if (b == 0) g_progress[(tag & 1) ^ 1] = 0;
                int last = 0;
#pragma unroll 1
                for (unsigned n = 0; n < SPIN_LIMIT; n++) {
                    const int p = pace[0];
                    unsigned all;
                    if (p != last) all = atomicAdd(ctr, (unsigned)(p - last)) + (unsigned)(p - last);
                    else asm volatile("ld.relaxed.gpu.global.u32 %0, [%1];" : "=r"(all) : "l"(ctr) : "memory");
                    last = p;
                    const float d = (float)(p - n_tiles) - (float)((int)all - TOTAL_TILES) * (1.0f / N_ATTN);
                    pace[1] = min(max(__float2int_rn((float)MAXFLY - PACE_K * (d - PACE_D0)), CAP_LO), CAP_HI);
                    if (p >= n_tiles) break;
                }
            }
            return;
        }
        if (warp == NCW + 2 && is_attn) {
            asm volatile("ld.relaxed.gpu.global.u32 %0, [%1];" : "=r"(tag) : "l"(&g_epoch) : "memory");
            const float gate = warp_gate(x, gate_w, lane);
            tag += 1;
            named_bar_sync(BAR_KDONE, 288);
            const bool dn = b < N_DOWN;
            const uint4* sp = &g_stats[h * 32 + lane];
            const uint4* gp = &g_gx[(dn ? b : 0) * 64 + (lane >> 3) * 16 + (lane & 7)];
            uint64_t v[3][2];
            unsigned n = 0;
            while (true) {
                asm volatile("ld.relaxed.gpu.global.v2.b64 {%0, %1}, [%2];" : "=l"(v[0][0]), "=l"(v[0][1]) : "l"(sp) : "memory");
                asm volatile("ld.relaxed.gpu.global.v2.b64 {%0, %1}, [%2];" : "=l"(v[1][0]), "=l"(v[1][1]) : "l"(gp) : "memory");
                asm volatile("ld.relaxed.gpu.global.v2.b64 {%0, %1}, [%2];" : "=l"(v[2][0]), "=l"(v[2][1]) : "l"(gp + 8) : "memory");
                bool ok = true;
#pragma unroll
                for (int k = 0; k < 3; k++)
                    ok = ok && (uint32_t)(v[k][0] >> 32) == tag && (uint32_t)(v[k][1] >> 32) == tag;
                if (__all_sync(0xffffffffu, ok) || ++n > SPIN_LIMIT) break;
            }
            {
                float g0 = __uint_as_float((uint32_t)v[1][0]), g1 = __uint_as_float((uint32_t)v[1][1]);
                float u0 = __uint_as_float((uint32_t)v[2][0]), u1 = __uint_as_float((uint32_t)v[2][1]);
#pragma unroll
                for (int o = 8; o <= 16; o <<= 1) {
                    g0 += __shfl_xor_sync(0xffffffffu, g0, o);
                    g1 += __shfl_xor_sync(0xffffffffu, g1, o);
                    u0 += __shfl_xor_sync(0xffffffffu, u0, o);
                    u1 += __shfl_xor_sync(0xffffffffu, u1, o);
                }
                const float h0 = dn ? g0 * u0 * (1.0f - gate) : 0.f;
                const float h1 = dn ? g1 * u1 * (1.0f - gate) : 0.f;
                uint32_t* bfrag_s = reinterpret_cast<uint32_t*>(smem + SM_BFRAG);
                const __nv_bfloat162 hi = __floats2bfloat162_rn(h0, h1);
                const __nv_bfloat162 lo = __floats2bfloat162_rn(h0 - __low2float(hi), h1 - __high2float(hi));
                const int row = lane >> 3;
                bfrag_s[row * 72 + 64 + (lane & 7)] = row == 0 ? *reinterpret_cast<const uint32_t*>(&hi)
                                                    : row == 1 ? *reinterpret_cast<const uint32_t*>(&lo) : 0u;
                bfrag_s[(row + 4) * 72 + 64 + (lane & 7)] = 0u;
            }
            {
                const float mw = __uint_as_float((uint32_t)v[0][0]), lw = __uint_as_float((uint32_t)v[0][1]);
                float mh = mw;
#pragma unroll
                for (int o = 16; o > 0; o >>= 1) mh = fmaxf(mh, __shfl_xor_sync(0xffffffffu, mh, o));
                const float e = exp2f(mw - mh);
                float lh = lw * e;
#pragma unroll
                for (int o = 16; o > 0; o >>= 1) lh += __shfl_xor_sync(0xffffffffu, lh, o);
                if ((lane >> 3) == split) fw_s[lane & 7] = e / lh * gate;
            }
            named_bar_sync(BAR_SCALE, 288);
        }
        return;
    }

    uint4 wv[8], xa, xb;
    if (is_attn) {
        if (tid < 64) st_pkt(&g_qx[b * 64 + tid], 0.f, 0.f, 0u);
        const int row0 = split * 128 + warp * 16;
        const __nv_bfloat16* wp = wq + (size_t)(row0 + (lane >> 4)) * (NH * DH) + h * DH + (lane & 15) * 8;
#pragma unroll
        for (int i = 0; i < 8; i++) wv[i] = ldg128(wp + (size_t)(2 * i) * (NH * DH));
        xa = ldg128(x + row0); xb = ldg128(x + row0 + 8);
    }
    asm volatile("ld.relaxed.gpu.global.u32 %0, [%1];" : "=r"(tag) : "l"(&g_epoch) : "memory");
    asm volatile("setmaxnreg.inc.sync.aligned.u32 232;");
    int s = 0;
    uint32_t ph = 0;
    auto advance = [&]() {
        __syncwarp();
        if (lane == 0) mbar_arrive(bar_empty + 8 * s);
        if (++s == NSTAGES) { s = 0; ph ^= 1; }
    };

    if (!is_attn) {
        float* x_s = reinterpret_cast<float*>(smem + SM_GX);
        {
            const uint32_t xx = *reinterpret_cast<const uint32_t*>(x + 2 * tid);
            *reinterpret_cast<float2*>(x_s + 2 * tid) = make_float2(bf_lo(xx), bf_hi(xx));
        }
        named_bar_sync(BAR_INIT, 320);
        tag += 1;
        const int gj = b - N_ATTN;
        {
            const bool act = tid < 172;
            const uint32_t off = act ? tid * 16 : 0;
            float ag[8], au[8];
#pragma unroll
            for (int j = 0; j < 8; j++) ag[j] = au[j] = 0.f;
#pragma unroll 1
            for (int it = 0; it < GU_TILES / 2; it++) {
                const float4 p = *reinterpret_cast<const float4*>(x_s + gj * 128 + it * GU_ROWS);
                {
                    mbar_wait(bar_full + 8 * s, ph);
                    const uint32_t a = sbase + SM_RING + s * TILE_BYTES + off;
                    const uint4 v0 = lds128(a), v1 = lds128(a + GU_PITCH), v2 = lds128(a + 2 * GU_PITCH),
                                v3 = lds128(a + 3 * GU_PITCH);
                    axpy8(ag, p.x, v0); axpy8(ag, p.y, v1); axpy8(ag, p.z, v2); axpy8(ag, p.w, v3);
                    advance();
                }
                {
                    mbar_wait(bar_full + 8 * s, ph);
                    const uint32_t a = sbase + SM_RING + s * TILE_BYTES + off;
                    const uint4 v0 = lds128(a), v1 = lds128(a + GU_PITCH), v2 = lds128(a + 2 * GU_PITCH),
                                v3 = lds128(a + 3 * GU_PITCH);
                    axpy8(au, p.x, v0); axpy8(au, p.y, v1); axpy8(au, p.z, v2); axpy8(au, p.w, v3);
                    advance();
                }
            }
            if (act) {
                uint4* gp = &g_gx[(tid >> 1) * 64 + gj * 16 + (tid & 1) * 4];
#pragma unroll
                for (int k = 0; k < 4; k++) {
                    st_pkt(gp + k, ag[2 * k], ag[2 * k + 1], tag);
                    st_pkt(gp + 8 + k, au[2 * k], au[2 * k + 1], tag);
                }
            }
        }
        if (tid == 0) PROF(5);
        return;
    }

    const int g = lane >> 2, t = lane & 3;
    float* opart_s = reinterpret_cast<float*>(smem + SM_OPART);
    uint32_t* bfrag_s = reinterpret_cast<uint32_t*>(smem + SM_BFRAG);
    float q[8];
    {
        named_bar_sync(BAR_INIT, 320);
        const uint32_t xw[8] = {xa.x, xa.y, xa.z, xa.w, xb.x, xb.y, xb.z, xb.w};
        float acc[8];
#pragma unroll
        for (int j = 0; j < 8; j++) acc[j] = 0.f;
#pragma unroll
        for (int i = 0; i < 8; i++) axpy8(acc, lane >= 16 ? bf_hi(xw[i]) : bf_lo(xw[i]), wv[i]);
#pragma unroll
        for (int j = 0; j < 8; j++) acc[j] += __shfl_xor_sync(0xffffffffu, acc[j], 16);
        float* op = opart_s + warp * DH + (lane & 15) * 8 + (lane >> 4) * 4;
        *reinterpret_cast<float4*>(op) = lane >= 16 ? make_float4(acc[4], acc[5], acc[6], acc[7])
                                                    : make_float4(acc[0], acc[1], acc[2], acc[3]);
        tag += 1;
        named_bar_sync(BAR_CONS, NCW * 32);
        if (tid < 64) {
            float q0 = 0.f, q1 = 0.f;
#pragma unroll
            for (int ww = 0; ww < NCW; ww++) {
                const float2 v = *reinterpret_cast<const float2*>(opart_s + ww * DH + 2 * tid);
                q0 += v.x;
                q1 += v.y;
            }
            st_pkt(&g_qx[b * 64 + tid], q0, q1, tag);
        }
        if (tid == 0) PROF(6);
        float q0, q1;
        ld_pkt_wait(&g_qx[h * NSPLIT * 64 + tid], tag, q0, q1);
        float* qs = reinterpret_cast<float*>(smem + SM_QX);
        *reinterpret_cast<float2*>(qs + 2 * tid) = make_float2(q0, q1);
        named_bar_sync(BAR_CONS, NCW * 32);
        const float sc = 0.08838834764831845f * 1.4426950408889634f;
#pragma unroll
        for (int j = 0; j < 8; j++) q[j] = 0.f;
#pragma unroll
        for (int sp = 0; sp < NSPLIT; sp++) {
            const float4 a = *reinterpret_cast<const float4*>(qs + sp * DH + (lane & 15) * 8);
            const float4 c = *reinterpret_cast<const float4*>(qs + sp * DH + (lane & 15) * 8 + 4);
            q[0] += a.x; q[1] += a.y; q[2] += a.z; q[3] += a.w;
            q[4] += c.x; q[5] += c.y; q[6] += c.z; q[7] += c.w;
        }
#pragma unroll
        for (int j = 0; j < 8; j++) q[j] *= sc;
    }
    if (tid == 0) PROF(1);

    uint4 w[36];
    const uint32_t wf_off = (4 * t) * 1024 + warp * 128 + g * 16;
    const uint32_t my_off = warp * 2048 + lane * 16;
    float* p_s = reinterpret_cast<float*>(smem + SM_P) + warp * 256;
#pragma unroll
    for (int grp = 0; grp < 8; grp++) {
#pragma unroll 1
        for (int r = 0; r < 4; r++) {
            mbar_wait(bar_full + 8 * s, ph);
            const uint32_t a = sbase + SM_RING + s * TILE_BYTES + my_off;
            const uint4 k0 = lds128(a), k1 = lds128(a + 512), k2 = lds128(a + 1024), k3 = lds128(a + 1536);
            float s0 = dot8(k0, q), s1 = dot8(k1, q), s2 = dot8(k2, q), s3 = dot8(k3, q);
            advance();
            const bool b3 = lane & 8, b2 = lane & 4;
            float u0 = b3 ? s2 : s0, u1 = b3 ? s3 : s1;
            float v0 = b3 ? s0 : s2, v1 = b3 ? s1 : s3;
            u0 += __shfl_xor_sync(0xffffffffu, v0, 8);
            u1 += __shfl_xor_sync(0xffffffffu, v1, 8);
            float rr = b2 ? u1 : u0, r2 = b2 ? u0 : u1;
            rr += __shfl_xor_sync(0xffffffffu, r2, 4);
            rr += __shfl_xor_sync(0xffffffffu, rr, 2);
            rr += __shfl_xor_sync(0xffffffffu, rr, 1);
            if ((lane & 3) == 0) p_s[(grp * 4 + r) * 8 + (lane >> 2)] = rr;
        }
        {
            mbar_wait(bar_full + 8 * s, ph);
            const uint32_t a = sbase + SM_RING + s * TILE_BYTES + wf_off;
            w[grp * 4] = lds128(a); w[grp * 4 + 1] = lds128(a + 1024);
            w[grp * 4 + 2] = lds128(a + 2048); w[grp * 4 + 3] = lds128(a + 3072);
            to_afrag(w[grp * 4], w[grp * 4 + 1], w[grp * 4 + 2], w[grp * 4 + 3]);
            advance();
        }
    }
    if (b < N_DOWN) {
        mbar_wait(bar_full + 8 * s, ph);
        const uint32_t a = sbase + SM_RING + s * TILE_BYTES + wf_off;
        w[32] = lds128(a); w[33] = lds128(a + 1024); w[34] = lds128(a + 2048); w[35] = lds128(a + 3072);
        to_afrag(w[32], w[33], w[34], w[35]);
        advance();
    } else {
        w[32] = w[33] = w[34] = w[35] = make_uint4(0, 0, 0, 0);
    }
    __syncwarp();
    if (tid == 0) PROF(2);
    {
        float4 sa = *reinterpret_cast<float4*>(p_s + lane * 8);
        float4 sb = *reinterpret_cast<float4*>(p_s + lane * 8 + 4);
        float m = fmaxf(fmaxf(fmaxf(sa.x, sa.y), fmaxf(sa.z, sa.w)), fmaxf(fmaxf(sb.x, sb.y), fmaxf(sb.z, sb.w)));
#pragma unroll
        for (int o = 16; o > 0; o >>= 1) m = fmaxf(m, __shfl_xor_sync(0xffffffffu, m, o));
        sa.x = exp2f(sa.x - m); sa.y = exp2f(sa.y - m); sa.z = exp2f(sa.z - m); sa.w = exp2f(sa.w - m);
        sb.x = exp2f(sb.x - m); sb.y = exp2f(sb.y - m); sb.z = exp2f(sb.z - m); sb.w = exp2f(sb.w - m);
        float l = ((sa.x + sa.y) + (sa.z + sa.w)) + ((sb.x + sb.y) + (sb.z + sb.w));
#pragma unroll
        for (int o = 16; o > 0; o >>= 1) l += __shfl_xor_sync(0xffffffffu, l, o);
        *reinterpret_cast<float4*>(p_s + lane * 8) = sa;
        *reinterpret_cast<float4*>(p_s + lane * 8 + 4) = sb;
        if (lane == 0) st_pkt(&g_stats[h * 32 + split * 8 + warp], m, l, tag);
        named_bar_arrive(BAR_KDONE, 288);
        __syncwarp();
    }
    float acc[8];
#pragma unroll
    for (int j = 0; j < 8; j++) acc[j] = 0.f;
    float c[2][4][4];
#pragma unroll
    for (int u = 0; u < 2; u++)
#pragma unroll
        for (int j = 0; j < 4; j++) c[u][j][0] = c[u][j][1] = c[u][j][2] = c[u][j][3] = 0.f;
    const uint32_t* bf = bfrag_s + g * 72 + 2 * t;
    float fw = 0.f;
    const float* p_rd = p_s + (lane >> 4) * 4;
#pragma unroll 1
    for (int it = 0; it < NT; it++) {
        const float4 p = *reinterpret_cast<const float4*>(p_rd + it * 8);
        if (it == NT - TAIL_LEAD) {
            st_pkt(&g_slots[((tid >> 1) * N_ATTN + b) * 2 + (tid & 1)], 0.f, 0.f, 0u);
            named_bar_sync(BAR_SCALE, 288);
            fw = fw_s[warp];
            const uint2 bb = *reinterpret_cast<const uint2*>(bf + 64);
            mma16816(c[0][0], w[32].x, w[33].x, w[34].x, w[35].x, bb.x, bb.y);
            mma16816(c[0][1], w[32].y, w[33].y, w[34].y, w[35].y, bb.x, bb.y);
            mma16816(c[0][2], w[32].z, w[33].z, w[34].z, w[35].z, bb.x, bb.y);
            mma16816(c[0][3], w[32].w, w[33].w, w[34].w, w[35].w, bb.x, bb.y);
        }
        mbar_wait(bar_full + 8 * s, ph);
        CLK(0);
        const uint32_t a = sbase + SM_RING + s * TILE_BYTES + my_off;
        const uint4 v0 = lds128(a), v1 = lds128(a + 512), v2 = lds128(a + 1024), v3 = lds128(a + 1536);
        axpy8(acc, p.x, v0);
        axpy8(acc, p.y, v1);
        axpy8(acc, p.z, v2);
        axpy8(acc, p.w, v3);
        advance();
    }
    CLK(1);
    if (tid == 0) PROF(3);
    {
        const bool up = lane >= 16;
        float o[4];
#pragma unroll
        for (int j = 0; j < 4; j++) {
            const float keep = up ? acc[4 + j] : acc[j], send = up ? acc[j] : acc[4 + j];
            o[j] = (keep + __shfl_xor_sync(0xffffffffu, send, 16)) * fw;
        }
        const __nv_bfloat162 w0 = __floats2bfloat162_rn(o[0], o[1]), w1 = __floats2bfloat162_rn(o[2], o[3]);
        *reinterpret_cast<uint2*>(bfrag_s + warp * 72 + (lane & 15) * 4 + (lane >> 4) * 2) =
            make_uint2(*reinterpret_cast<const uint32_t*>(&w0), *reinterpret_cast<const uint32_t*>(&w1));
    }
    CLK(2);
    named_bar_sync(BAR_CONS, NCW * 32);
    CLK(4);
    {
#pragma unroll
        for (int ks = 0; ks < 8; ks++) {
            const uint2 bb = *reinterpret_cast<const uint2*>(bf + 8 * ks);
            mma16816(c[ks & 1][0], w[ks * 4].x, w[ks * 4 + 1].x, w[ks * 4 + 2].x, w[ks * 4 + 3].x, bb.x, bb.y);
            mma16816(c[ks & 1][1], w[ks * 4].y, w[ks * 4 + 1].y, w[ks * 4 + 2].y, w[ks * 4 + 3].y, bb.x, bb.y);
            mma16816(c[ks & 1][2], w[ks * 4].z, w[ks * 4 + 1].z, w[ks * 4 + 2].z, w[ks * 4 + 3].z, bb.x, bb.y);
            mma16816(c[ks & 1][3], w[ks * 4].w, w[ks * 4 + 1].w, w[ks * 4 + 2].w, w[ks * 4 + 3].w, bb.x, bb.y);
        }
        float ya[4], yb[4];
#pragma unroll
        for (int j = 0; j < 4; j++) {
            ya[j] = (c[0][j][0] + c[1][j][0]) + (c[0][j][1] + c[1][j][1]);
            yb[j] = (c[0][j][2] + c[1][j][2]) + (c[0][j][3] + c[1][j][3]);
        }
        const bool t1 = t & 2, t0 = t & 1;
        const float a0 = (t1 ? ya[2] : ya[0]) + __shfl_xor_sync(0xffffffffu, t1 ? ya[0] : ya[2], 2);
        const float a1 = (t1 ? ya[3] : ya[1]) + __shfl_xor_sync(0xffffffffu, t1 ? ya[1] : ya[3], 2);
        const float b0 = (t1 ? yb[2] : yb[0]) + __shfl_xor_sync(0xffffffffu, t1 ? yb[0] : yb[2], 2);
        const float b1 = (t1 ? yb[3] : yb[1]) + __shfl_xor_sync(0xffffffffu, t1 ? yb[1] : yb[3], 2);
        const float y0 = (t0 ? a1 : a0) + __shfl_xor_sync(0xffffffffu, t0 ? a0 : a1, 1);
        const float y1 = (t0 ? b1 : b0) + __shfl_xor_sync(0xffffffffu, t0 ? b0 : b1, 1);
        CLK(5);
        st_pkt(&g_slots[((tid >> 1) * N_ATTN + b) * 2 + (tid & 1)], y0, y1, tag);
    }
    CLK(6);
    if (tid == 0) PROF(4);
    if (warp < 2) {
        const uint4* sp = &g_slots[(b * N_ATTN + lane) * 2 + warp];
        float a0, a1;
        unsigned n = 0;
        while (true) {
            uint64_t v[4][2];
#pragma unroll
            for (int k = 0; k < 4; k++)
                asm volatile("ld.relaxed.gpu.global.v2.b64 {%0, %1}, [%2];"
                             : "=l"(v[k][0]), "=l"(v[k][1]) : "l"(sp + 64 * k) : "memory");
            bool ok = true;
            a0 = a1 = 0.f;
#pragma unroll
            for (int k = 0; k < 4; k++) {
                ok = ok && (uint32_t)(v[k][0] >> 32) == tag && (uint32_t)(v[k][1] >> 32) == tag;
                a0 += __uint_as_float((uint32_t)v[k][0]);
                a1 += __uint_as_float((uint32_t)v[k][1]);
            }
            if (ok || ++n > SPIN_LIMIT) break;
        }
        __syncwarp();
#pragma unroll
        for (int o = 16; o > 0; o >>= 1) {
            a0 += __shfl_xor_sync(0xffffffffu, a0, o);
            a1 += __shfl_xor_sync(0xffffffffu, a1, o);
        }
        if (lane == 0) {
            *reinterpret_cast<__nv_bfloat162*>(out + 4 * b + 2 * warp) = __floats2bfloat162_rn(a0, a1);
            if (b == 0 && warp == 0) g_epoch = tag;
            if (tid == 0) PROF(5);
        }
    }
}

}

extern "C" void kernel_launch(void* const* d_in, const int* in_sizes, int n_in, void* d_out, int out_size) {
    (void)in_sizes; (void)n_in; (void)out_size;
    const __nv_bfloat16* x      = (const __nv_bfloat16*)d_in[0];
    const __nv_bfloat16* kc     = (const __nv_bfloat16*)d_in[1];
    const __nv_bfloat16* vc     = (const __nv_bfloat16*)d_in[2];
    const __nv_bfloat16* wq     = (const __nv_bfloat16*)d_in[3];
    const __nv_bfloat16* wo     = (const __nv_bfloat16*)d_in[4];
    const __nv_bfloat16* w_gate = (const __nv_bfloat16*)d_in[6];
    const __nv_bfloat16* w_up   = (const __nv_bfloat16*)d_in[7];
    const __nv_bfloat16* w_down = (const __nv_bfloat16*)d_in[8];
    const __nv_bfloat16* gate_w = (const __nv_bfloat16*)d_in[9];

    cudaFuncSetAttribute(fused_decode_kernel, cudaFuncAttributeMaxDynamicSharedMemorySize, SM_TOTAL);
    fused_decode_kernel<<<N_CTA, NLAUNCH, SM_TOTAL>>>(x, kc, vc, wq, wo, w_gate, w_up, w_down, gate_w,
                                                     (__nv_bfloat16*)d_out);
}
```

```cpp
#include <cuda_runtime.h>
#include <cuda_bf16.h>
#include <stdint.h>

namespace {

constexpr int D_MODEL = 512;
constexpr int NH      = 32;
constexpr int SK      = 8192;
constexpr int DH      = 128;
constexpr int FF      = 1376;

constexpr int NSPLIT       = 4;
constexpr int N_ATTN       = NH * NSPLIT;
constexpr int N_GLU        = 4;
constexpr int N_CTA        = N_ATTN + N_GLU;
constexpr int N_DOWN       = FF / 16;
constexpr int GU_ROWS      = 4;
constexpr int GU_PITCH     = FF * 2;
constexpr int GU_BYTES     = GU_ROWS * GU_PITCH;
constexpr int GU_TILES     = 2 * (D_MODEL / N_GLU / GU_ROWS);
constexpr int TOTAL_TILES  = N_ATTN * (2 * (SK / NSPLIT / 64) + 8) + N_DOWN;
constexpr int KEYS_PER_CTA = SK / NSPLIT;
constexpr int TILE_KEYS    = 64;
constexpr int TILE_BYTES   = TILE_KEYS * DH * 2;
constexpr int NT           = KEYS_PER_CTA / TILE_KEYS;
#define NSTAGES 12
#define MAXFLY 4
#define CAP_LO 2
#define CAP_HI 6
#define PACE_K 1.0f
#define PACE_D0 0.4f
#define PACE_START MAXFLY
#define GLUFLY 8
#define TAIL_LEAD 12

constexpr int NCW          = 8;
constexpr int NLAUNCH      = (NCW + 4) * 32;
constexpr int BAR_SCALE = 1;
constexpr int BAR_CONS  = 2;
constexpr int BAR_INIT  = 3;
constexpr int BAR_KDONE = 5;

constexpr int SM_RING   = 0;
constexpr int SM_P      = SM_RING + NSTAGES * TILE_BYTES;
constexpr int SM_OPART  = SM_P + NCW * 256 * 4;
constexpr int SM_QX     = SM_OPART + NCW * DH * 4;
constexpr int SM_BFRAG  = SM_QX + NSPLIT * DH * 4;
constexpr int SM_FW     = SM_BFRAG + 8 * 72 * 4;
constexpr int SM_PACE   = SM_FW + 8 * 4;
constexpr int SM_BARS   = SM_PACE + 16;
constexpr int SM_TOTAL  = SM_BARS + 2 * NSTAGES * 8;
constexpr int SM_GX     = SM_P;

constexpr unsigned SPIN_LIMIT = 1u << 20;

__device__ unsigned int g_epoch;
__device__ unsigned int g_progress[2];
__device__ __align__(128) uint4 g_qx[NH * NSPLIT * 64];
__device__ __align__(128) uint4 g_stats[NH * 32];
__device__ __align__(128) uint4 g_gx[N_DOWN * 64];
__device__ __align__(128) uint4 g_slots[N_ATTN * N_ATTN * 2];

__device__ __forceinline__ uint32_t smem_u32(const void* p) { return (uint32_t)__cvta_generic_to_shared(p); }
__device__ __forceinline__ void mbar_init(uint32_t bar, uint32_t cnt) {
    asm volatile("mbarrier.init.shared::cta.b64 [%0], %1;" ::"r"(bar), "r"(cnt) : "memory");
}
__device__ __forceinline__ void mbar_expect_tx(uint32_t bar, uint32_t bytes) {
    asm volatile("mbarrier.arrive.expect_tx.shared::cta.b64 _, [%0], %1;" ::"r"(bar), "r"(bytes) : "memory");
}
__device__ __forceinline__ void mbar_arrive(uint32_t bar) {
    asm volatile("mbarrier.arrive.shared::cta.b64 _, [%0];" ::"r"(bar) : "memory");
}
__device__ __forceinline__ bool mbar_try_wait(uint32_t bar, uint32_t parity) {
    uint32_t ok;
    asm volatile(
        "{\n\t.reg .pred p;\n\t"
        "mbarrier.try_wait.parity.shared::cta.b64 p, [%1], %2;\n\t"
        "selp.b32 %0, 1, 0, p;\n\t}"
        : "=r"(ok)
        : "r"(bar), "r"(parity)
        : "memory");
    return ok != 0;
}
__device__ __forceinline__ void mbar_wait(uint32_t bar, uint32_t parity) {
    unsigned n = 0;
    while (!mbar_try_wait(bar, parity)) {
        if (++n > SPIN_LIMIT) break;
    }
}
__device__ __forceinline__ void bulk_load(uint32_t dst, const void* src, uint32_t bytes, uint32_t bar) {
    asm volatile("cp.async.bulk.shared::cluster.global.mbarrier::complete_tx::bytes [%0], [%1], %2, [%3];"
                 ::"r"(dst), "l"(src), "r"(bytes), "r"(bar) : "memory");
}
__device__ __forceinline__ void bulk_load_hint(uint32_t dst, const void* src, uint32_t bytes, uint32_t bar, uint64_t pol) {
    asm volatile("cp.async.bulk.shared::cluster.global.mbarrier::complete_tx::bytes.L2::cache_hint [%0], [%1], %2, [%3], %4;"
                 ::"r"(dst), "l"(src), "r"(bytes), "r"(bar), "l"(pol) : "memory");
}
__device__ __forceinline__ uint4 ldg128(const void* p) {
    uint4 v;
    asm volatile("ld.global.nc.L1::no_allocate.v4.u32 {%0,%1,%2,%3}, [%4];"
                 : "=r"(v.x), "=r"(v.y), "=r"(v.z), "=r"(v.w) : "l"(p));
    return v;
}
__device__ __forceinline__ uint4 lds128(uint32_t a) {
    uint4 v;
    asm volatile("ld.shared.v4.u32 {%0,%1,%2,%3}, [%4];" : "=r"(v.x), "=r"(v.y), "=r"(v.z), "=r"(v.w) : "r"(a));
    return v;
}
__device__ __forceinline__ void st_pkt(uint4* p, float a, float b, uint32_t tag) {
    uint64_t lo = ((uint64_t)tag << 32) | __float_as_uint(a);
    uint64_t hi = ((uint64_t)tag << 32) | __float_as_uint(b);
    asm volatile("st.relaxed.gpu.global.v2.b64 [%0], {%1, %2};" ::"l"(p), "l"(lo), "l"(hi) : "memory");
}
__device__ __forceinline__ void ld_pkt_wait(const uint4* p, uint32_t tag, float& a, float& b) {
    uint64_t lo, hi;
    unsigned n = 0;
    while (true) {
        asm volatile("ld.relaxed.gpu.global.v2.b64 {%0, %1}, [%2];" : "=l"(lo), "=l"(hi) : "l"(p) : "memory");
        if ((uint32_t)(lo >> 32) == tag && (uint32_t)(hi >> 32) == tag) break;
        if (++n > SPIN_LIMIT) break;
    }
    a = __uint_as_float((uint32_t)lo);
    b = __uint_as_float((uint32_t)hi);
}
__device__ __forceinline__ void named_bar_sync(int id, int nthreads) {
    asm volatile("bar.sync %0, %1;" ::"r"(id), "r"(nthreads) : "memory");
}
__device__ __forceinline__ void named_bar_arrive(int id, int nthreads) {
    asm volatile("bar.arrive %0, %1;" ::"r"(id), "r"(nthreads) : "memory");
}
__device__ __forceinline__ float bf_lo(uint32_t w) { return __uint_as_float(w << 16); }
__device__ __forceinline__ float bf_hi(uint32_t w) { return __uint_as_float(w & 0xffff0000u); }
__device__ __forceinline__ void mma16816(float (&c)[4], uint32_t a0, uint32_t a1, uint32_t a2, uint32_t a3,
                                         uint32_t b0, uint32_t b1) {
    asm volatile(
        "mma.sync.aligned.m16n8k16.row.col.f32.bf16.bf16.f32 {%0,%1,%2,%3}, {%4,%5,%6,%7}, {%8,%9}, {%0,%1,%2,%3};"
        : "+f"(c[0]), "+f"(c[1]), "+f"(c[2]), "+f"(c[3])
        : "r"(a0), "r"(a1), "r"(a2), "r"(a3), "r"(b0), "r"(b1));
}
__device__ __forceinline__ uint32_t prmt(uint32_t a, uint32_t b, uint32_t sel) {
    uint32_t r;
    asm("prmt.b32 %0, %1, %2, %3;" : "=r"(r) : "r"(a), "r"(b), "r"(sel));
    return r;
}
__device__ __forceinline__ void to_afrag(uint4& w0, uint4& w1, uint4& w2, uint4& w3) {
#define TO_AFRAG_1(f)                                   \
    {                                                   \
        uint32_t a0 = prmt(w0.f, w1.f, 0x5410);         \
        uint32_t a1 = prmt(w0.f, w1.f, 0x7632);         \
        uint32_t a2 = prmt(w2.f, w3.f, 0x5410);         \
        uint32_t a3 = prmt(w2.f, w3.f, 0x7632);         \
        w0.f = a0; w1.f = a1; w2.f = a2; w3.f = a3;     \
    }
    TO_AFRAG_1(x) TO_AFRAG_1(y) TO_AFRAG_1(z) TO_AFRAG_1(w)
#undef TO_AFRAG_1
}
__device__ __forceinline__ float dot8(const uint4& k, const float (&q)[8]) {
    float s0 = bf_lo(k.x) * q[0];
    float s1 = bf_hi(k.x) * q[1];
    s0 = fmaf(bf_lo(k.y), q[2], s0);
    s1 = fmaf(bf_hi(k.y), q[3], s1);
    s0 = fmaf(bf_lo(k.z), q[4], s0);
    s1 = fmaf(bf_hi(k.z), q[5], s1);
    s0 = fmaf(bf_lo(k.w), q[6], s0);
    s1 = fmaf(bf_hi(k.w), q[7], s1);
    return s0 + s1;
}
__device__ __forceinline__ void axpy8(float (&acc)[8], float p, const uint4& v) {
    acc[0] = fmaf(p, bf_lo(v.x), acc[0]);
    acc[1] = fmaf(p, bf_hi(v.x), acc[1]);
    acc[2] = fmaf(p, bf_lo(v.y), acc[2]);
    acc[3] = fmaf(p, bf_hi(v.y), acc[3]);
    acc[4] = fmaf(p, bf_lo(v.z), acc[4]);
    acc[5] = fmaf(p, bf_hi(v.z), acc[5]);
    acc[6] = fmaf(p, bf_lo(v.w), acc[6]);
    acc[7] = fmaf(p, bf_hi(v.w), acc[7]);
}
__device__ __forceinline__ float warp_gate(const __nv_bfloat16* x, const __nv_bfloat16* gw, int lane) {
    uint4 xa = ldg128(x + lane * 16), xb = ldg128(x + lane * 16 + 8);
    uint4 ga = ldg128(gw + lane * 16), gb = ldg128(gw + lane * 16 + 8);
    float s = bf_lo(xa.x) * bf_lo(ga.x) + bf_hi(xa.x) * bf_hi(ga.x) + bf_lo(xa.y) * bf_lo(ga.y) + bf_hi(xa.y) * bf_hi(ga.y)
            + bf_lo(xa.z) * bf_lo(ga.z) + bf_hi(xa.z) * bf_hi(ga.z) + bf_lo(xa.w) * bf_lo(ga.w) + bf_hi(xa.w) * bf_hi(ga.w)
            + bf_lo(xb.x) * bf_lo(gb.x) + bf_hi(xb.x) * bf_hi(gb.x) + bf_lo(xb.y) * bf_lo(gb.y) + bf_hi(xb.y) * bf_hi(gb.y)
            + bf_lo(xb.z) * bf_lo(gb.z) + bf_hi(xb.z) * bf_hi(gb.z) + bf_lo(xb.w) * bf_lo(gb.w) + bf_hi(xb.w) * bf_hi(gb.w);
#pragma unroll
    for (int o = 16; o > 0; o >>= 1) s += __shfl_xor_sync(0xffffffffu, s, o);
    return 1.0f / (1.0f + __expf(-s));
}

__global__ void __launch_bounds__(NLAUNCH, 1)
fused_decode_kernel(const __nv_bfloat16* __restrict__ x, const __nv_bfloat16* __restrict__ kc,
                    const __nv_bfloat16* __restrict__ vc, const __nv_bfloat16* __restrict__ wq,
                    const __nv_bfloat16* __restrict__ wo, const __nv_bfloat16* __restrict__ w_gate,
                    const __nv_bfloat16* __restrict__ w_up, const __nv_bfloat16* __restrict__ w_down,
                    const __nv_bfloat16* __restrict__ gate_w, __nv_bfloat16* __restrict__ out) {
    extern __shared__ __align__(128) unsigned char smem[];
    const int tid = threadIdx.x, lane = tid & 31;
    const int warp = __shfl_sync(0xffffffffu, tid >> 5, 0);
    const int wg = __shfl_sync(0xffffffffu, tid >> 7, 0);
    const int b = blockIdx.x;
    const uint32_t sbase = smem_u32(smem);
    const bool is_attn = b < N_ATTN;
    const int h = b / NSPLIT, split = b % NSPLIT;
    const uint32_t bar_full = sbase + SM_BARS, bar_empty = bar_full + NSTAGES * 8;
    float* fw_s = reinterpret_cast<float*>(smem + SM_FW);
    uint32_t tag;

    if (wg == 2) {
        asm volatile("setmaxnreg.dec.sync.aligned.u32 40;");
        volatile int* pace = reinterpret_cast<volatile int*>(smem + SM_PACE);
        const int n_dn = (b < N_DOWN) ? 1 : 0;
        const int n_tiles = is_attn ? 2 * NT + 8 + n_dn : GU_TILES;
        if (warp == NCW) {
            const size_t off = (size_t)b * KEYS_PER_CTA * DH;
            const unsigned char* ksrc = reinterpret_cast<const unsigned char*>(kc + off);
            const unsigned char* vsrc = reinterpret_cast<const unsigned char*>(vc + off);
            const unsigned char* wosrc = reinterpret_cast<const unsigned char*>(wo + (size_t)h * DH * D_MODEL);
            const int gj = b - N_ATTN;
            const int max_fly = is_attn ? MAXFLY : GLUFLY;
            uint64_t pol;
            asm volatile("createpolicy.fractional.L2::evict_first.b64 %0, 1.0;" : "=l"(pol));
            auto issue = [&](int i, int s) {
                const uint32_t dst = sbase + SM_RING + s * TILE_BYTES, bar = bar_full + 8 * s;
                if (is_attn) {
                    mbar_expect_tx(bar, TILE_BYTES);
                    if (i < 40) {
                        const int grp = i / 5, r = i - grp * 5;
                        if (r < 4) bulk_load_hint(dst, ksrc + (size_t)(grp * 4 + r) * TILE_BYTES, TILE_BYTES, bar, pol);
                        else       bulk_load(dst, wosrc + (size_t)grp * TILE_BYTES, TILE_BYTES, bar);
                    } else {
                        const unsigned char* src =
                            (i < 40 + n_dn) ? reinterpret_cast<const unsigned char*>(w_down + (size_t)b * 16 * D_MODEL)
                                            : vsrc + (size_t)(i - 40 - n_dn) * TILE_BYTES;
                        bulk_load_hint(dst, src, TILE_BYTES, bar, pol);
                    }
                } else {
                    mbar_expect_tx(bar, GU_BYTES);
                    bulk_load_hint(dst, ((i & 1) ? w_up : w_gate) + (size_t)(gj * 128 + (i >> 1) * GU_ROWS) * FF,
                                   GU_BYTES, bar, pol);
                }
            };
            if (lane == 0) {
#pragma unroll
                for (int s = 0; s < NSTAGES; s++) mbar_init(bar_full + 8 * s, 1);
                asm volatile("fence.mbarrier_init.release.cluster;" ::: "memory");
                asm volatile("fence.proxy.async.shared::cta;" ::: "memory");
#pragma unroll 1
                for (int s = 0; s < max_fly; s++) issue(s, s);
#pragma unroll
                for (int s = 0; s < NSTAGES; s++) mbar_init(bar_empty + 8 * s, NCW);
                pace[0] = max_fly;
                pace[1] = max_fly;
            }
            __syncwarp();
            named_bar_arrive(BAR_INIT, 320);
            if (lane == 0) {
                int s = max_fly, sf = 0, landed = 0;
                uint32_t ph = 1, phf = 0;
#pragma unroll 1
                for (int i = max_fly; i < n_tiles; i++) {
                    const int lag = pace[1];
                    while (landed <= i - lag) {
                        mbar_wait(bar_full + 8 * sf, phf);
                        if (++sf == NSTAGES) { sf = 0; phf ^= 1; }
                        landed++;
                    }
                    mbar_wait(bar_empty + 8 * s, ph);
                    issue(i, s);
                    pace[0] = i + 1;
                    if (++s == NSTAGES) { s = 0; ph ^= 1; }
                }
            }
            return;
        }
        if (warp == NCW + 1) {
            asm volatile("ld.relaxed.gpu.global.u32 %0, [%1];" : "=r"(tag) : "l"(&g_epoch) : "memory");
            named_bar_sync(BAR_INIT, 320);
            if (lane == 0 && is_attn) {
                unsigned* ctr = &g_progress[tag & 1];
                if (b == 0) g_progress[(tag & 1) ^ 1] = 0;
                int last = 0;
#pragma unroll 1
                for (unsigned n = 0; n < SPIN_LIMIT; n++) {
                    const int p = pace[0];
                    unsigned all;
                    if (p != last) all = atomicAdd(ctr, (unsigned)(p - last)) + (unsigned)(p - last);
                    else asm volatile("ld.relaxed.gpu.global.u32 %0, [%1];" : "=r"(all) : "l"(ctr) : "memory");
                    last = p;
                    const float d = (float)(p - n_tiles) - (float)((int)all - TOTAL_TILES) * (1.0f / N_ATTN);
                    if (all >= (unsigned)(N_ATTN * PACE_START))
                        pace[1] = min(max(__float2int_rn((float)MAXFLY - PACE_K * (d - PACE_D0)), CAP_LO), CAP_HI);
                    if (p >= n_tiles) break;
                }
            }
            return;
        }
        if (warp == NCW + 2 && is_attn) {
            asm volatile("ld.relaxed.gpu.global.u32 %0, [%1];" : "=r"(tag) : "l"(&g_epoch) : "memory");
            const float gate = warp_gate(x, gate_w, lane);
            tag += 1;
            named_bar_sync(BAR_KDONE, 288);
            const bool dn = b < N_DOWN;
            const uint4* sp = &g_stats[h * 32 + lane];
            const uint4* gp = &g_gx[(dn ? b : 0) * 64 + (lane >> 3) * 16 + (lane & 7)];
            uint64_t v[3][2];
            unsigned n = 0;
            while (true) {
                asm volatile("ld.relaxed.gpu.global.v2.b64 {%0, %1}, [%2];" : "=l"(v[0][0]), "=l"(v[0][1]) : "l"(sp) : "memory");
                asm volatile("ld.relaxed.gpu.global.v2.b64 {%0, %1}, [%2];" : "=l"(v[1][0]), "=l"(v[1][1]) : "l"(gp) : "memory");
                asm volatile("ld.relaxed.gpu.global.v2.b64 {%0, %1}, [%2];" : "=l"(v[2][0]), "=l"(v[2][1]) : "l"(gp + 8) : "memory");
                bool ok = true;
#pragma unroll
                for (int k = 0; k < 3; k++)
                    ok = ok && (uint32_t)(v[k][0] >> 32) == tag && (uint32_t)(v[k][1] >> 32) == tag;
                if (__all_sync(0xffffffffu, ok) || ++n > SPIN_LIMIT) break;
            }
            {
                float g0 = __uint_as_float((uint32_t)v[1][0]), g1 = __uint_as_float((uint32_t)v[1][1]);
                float u0 = __uint_as_float((uint32_t)v[2][0]), u1 = __uint_as_float((uint32_t)v[2][1]);
#pragma unroll
                for (int o = 8; o <= 16; o <<= 1) {
                    g0 += __shfl_xor_sync(0xffffffffu, g0, o);
                    g1 += __shfl_xor_sync(0xffffffffu, g1, o);
                    u0 += __shfl_xor_sync(0xffffffffu, u0, o);
                    u1 += __shfl_xor_sync(0xffffffffu, u1, o);
                }
                const float h0 = dn ? g0 * u0 * (1.0f - gate) : 0.f;
                const float h1 = dn ? g1 * u1 * (1.0f - gate) : 0.f;
                uint32_t* bfrag_s = reinterpret_cast<uint32_t*>(smem + SM_BFRAG);
                const __nv_bfloat162 hi = __floats2bfloat162_rn(h0, h1);
                const __nv_bfloat162 lo = __floats2bfloat162_rn(h0 - __low2float(hi), h1 - __high2float(hi));
                const int row = lane >> 3;
                bfrag_s[row * 72 + 64 + (lane & 7)] = row == 0 ? *reinterpret_cast<const uint32_t*>(&hi)
                                                    : row == 1 ? *reinterpret_cast<const uint32_t*>(&lo) : 0u;
                bfrag_s[(row + 4) * 72 + 64 + (lane & 7)] = 0u;
            }
            {
                const float mw = __uint_as_float((uint32_t)v[0][0]), lw = __uint_as_float((uint32_t)v[0][1]);
                float mh = mw;
#pragma unroll
                for (int o = 16; o > 0; o >>= 1) mh = fmaxf(mh, __shfl_xor_sync(0xffffffffu, mh, o));
                const float e = exp2f(mw - mh);
                float lh = lw * e;
#pragma unroll
                for (int o = 16; o > 0; o >>= 1) lh += __shfl_xor_sync(0xffffffffu, lh, o);
                if ((lane >> 3) == split) fw_s[lane & 7] = e / lh * gate;
            }
            named_bar_sync(BAR_SCALE, 288);
        }
        return;
    }

    uint4 wv[8], xa, xb;
    if (is_attn) {
        if (tid < 64) st_pkt(&g_qx[b * 64 + tid], 0.f, 0.f, 0u);
        const int row0 = split * 128 + warp * 16;
        const __nv_bfloat16* wp = wq + (size_t)(row0 + (lane >> 4)) * (NH * DH) + h * DH + (lane & 15) * 8;
#pragma unroll
        for (int i = 0; i < 8; i++) wv[i] = ldg128(wp + (size_t)(2 * i) * (NH * DH));
        xa = ldg128(x + row0); xb = ldg128(x + row0 + 8);
    }
    asm volatile("ld.relaxed.gpu.global.u32 %0, [%1];" : "=r"(tag) : "l"(&g_epoch) : "memory");
    asm volatile("setmaxnreg.inc.sync.aligned.u32 232;");
    int s = 0;
    uint32_t ph = 0;
    auto advance = [&]() {
        __syncwarp();
        if (lane == 0) mbar_arrive(bar_empty + 8 * s);
        if (++s == NSTAGES) { s = 0; ph ^= 1; }
    };

    if (!is_attn) {
        float* x_s = reinterpret_cast<float*>(smem + SM_GX);
        {
            const uint32_t xx = *reinterpret_cast<const uint32_t*>(x + 2 * tid);
            *reinterpret_cast<float2*>(x_s + 2 * tid) = make_float2(bf_lo(xx), bf_hi(xx));
        }
        named_bar_sync(BAR_INIT, 320);
        tag += 1;
        const int gj = b - N_ATTN;
        {
            const bool act = tid < 172;
            const uint32_t off = act ? tid * 16 : 0;
            float ag[8], au[8];
#pragma unroll
            for (int j = 0; j < 8; j++) ag[j] = au[j] = 0.f;
#pragma unroll 1
            for (int it = 0; it < GU_TILES / 2; it++) {
                const float4 p = *reinterpret_cast<const float4*>(x_s + gj * 128 + it * GU_ROWS);
                {
                    mbar_wait(bar_full + 8 * s, ph);
                    const uint32_t a = sbase + SM_RING + s * TILE_BYTES + off;
                    const uint4 v0 = lds128(a), v1 = lds128(a + GU_PITCH), v2 = lds128(a + 2 * GU_PITCH),
                                v3 = lds128(a + 3 * GU_PITCH);
                    axpy8(ag, p.x, v0); axpy8(ag, p.y, v1); axpy8(ag, p.z, v2); axpy8(ag, p.w, v3);
                    advance();
                }
                {
                    mbar_wait(bar_full + 8 * s, ph);
                    const uint32_t a = sbase + SM_RING + s * TILE_BYTES + off;
                    const uint4 v0 = lds128(a), v1 = lds128(a + GU_PITCH), v2 = lds128(a + 2 * GU_PITCH),
                                v3 = lds128(a + 3 * GU_PITCH);
                    axpy8(au, p.x, v0); axpy8(au, p.y, v1); axpy8(au, p.z, v2); axpy8(au, p.w, v3);
                    advance();
                }
            }
            if (act) {
                uint4* gp = &g_gx[(tid >> 1) * 64 + gj * 16 + (tid & 1) * 4];
#pragma unroll
                for (int k = 0; k < 4; k++) {
                    st_pkt(gp + k, ag[2 * k], ag[2 * k + 1], tag);
                    st_pkt(gp + 8 + k, au[2 * k], au[2 * k + 1], tag);
                }
            }
        }
        return;
    }

    const int g = lane >> 2, t = lane & 3;
    float* opart_s = reinterpret_cast<float*>(smem + SM_OPART);
    uint32_t* bfrag_s = reinterpret_cast<uint32_t*>(smem + SM_BFRAG);
    float q[8];
    {
        named_bar_sync(BAR_INIT, 320);
        const uint32_t xw[8] = {xa.x, xa.y, xa.z, xa.w, xb.x, xb.y, xb.z, xb.w};
        float acc[8];
#pragma unroll
        for (int j = 0; j < 8; j++) acc[j] = 0.f;
#pragma unroll
        for (int i = 0; i < 8; i++) axpy8(acc, lane >= 16 ? bf_hi(xw[i]) : bf_lo(xw[i]), wv[i]);
#pragma unroll
        for (int j = 0; j < 8; j++) acc[j] += __shfl_xor_sync(0xffffffffu, acc[j], 16);
        float* op = opart_s + warp * DH + (lane & 15) * 8 + (lane >> 4) * 4;
        *reinterpret_cast<float4*>(op) = lane >= 16 ? make_float4(acc[4], acc[5], acc[6], acc[7])
                                                    : make_float4(acc[0], acc[1], acc[2], acc[3]);
        tag += 1;
        named_bar_sync(BAR_CONS, NCW * 32);
        if (tid < 64) {
            float q0 = 0.f, q1 = 0.f;
#pragma unroll
            for (int ww = 0; ww < NCW; ww++) {
                const float2 v = *reinterpret_cast<const float2*>(opart_s + ww * DH + 2 * tid);
                q0 += v.x;
                q1 += v.y;
            }
            st_pkt(&g_qx[b * 64 + tid], q0, q1, tag);
        }
        float q0, q1;
        ld_pkt_wait(&g_qx[h * NSPLIT * 64 + tid], tag, q0, q1);
        float* qs = reinterpret_cast<float*>(smem + SM_QX);
        *reinterpret_cast<float2*>(qs + 2 * tid) = make_float2(q0, q1);
        named_bar_sync(BAR_CONS, NCW * 32);
        const float sc = 0.08838834764831845f * 1.4426950408889634f;
#pragma unroll
        for (int j = 0; j < 8; j++) q[j] = 0.f;
#pragma unroll
        for (int sp = 0; sp < NSPLIT; sp++) {
            const float4 a = *reinterpret_cast<const float4*>(qs + sp * DH + (lane & 15) * 8);
            const float4 c = *reinterpret_cast<const float4*>(qs + sp * DH + (lane & 15) * 8 + 4);
            q[0] += a.x; q[1] += a.y; q[2] += a.z; q[3] += a.w;
            q[4] += c.x; q[5] += c.y; q[6] += c.z; q[7] += c.w;
        }
#pragma unroll
        for (int j = 0; j < 8; j++) q[j] *= sc;
    }

    uint4 w[36];
    const uint32_t wf_off = (4 * t) * 1024 + warp * 128 + g * 16;
    const uint32_t my_off = warp * 2048 + lane * 16;
    float* p_s = reinterpret_cast<float*>(smem + SM_P) + warp * 256;
#pragma unroll
    for (int grp = 0; grp < 8; grp++) {
#pragma unroll 1
        for (int r = 0; r < 4; r++) {
            mbar_wait(bar_full + 8 * s, ph);
            const uint32_t a = sbase + SM_RING + s * TILE_BYTES + my_off;
            const uint4 k0 = lds128(a), k1 = lds128(a + 512), k2 = lds128(a + 1024), k3 = lds128(a + 1536);
            float s0 = dot8(k0, q), s1 = dot8(k1, q), s2 = dot8(k2, q), s3 = dot8(k3, q);
            advance();
            const bool b3 = lane & 8, b2 = lane & 4;
            float u0 = b3 ? s2 : s0, u1 = b3 ? s3 : s1;
            float v0 = b3 ? s0 : s2, v1 = b3 ? s1 : s3;
            u0 += __shfl_xor_sync(0xffffffffu, v0, 8);
            u1 += __shfl_xor_sync(0xffffffffu, v1, 8);
            float rr = b2 ? u1 : u0, r2 = b2 ? u0 : u1;
            rr += __shfl_xor_sync(0xffffffffu, r2, 4);
            rr += __shfl_xor_sync(0xffffffffu, rr, 2);
            rr += __shfl_xor_sync(0xffffffffu, rr, 1);
            if ((lane & 3) == 0) p_s[(grp * 4 + r) * 8 + (lane >> 2)] = rr;
        }
        {
            mbar_wait(bar_full + 8 * s, ph);
            const uint32_t a = sbase + SM_RING + s * TILE_BYTES + wf_off;
            w[grp * 4] = lds128(a); w[grp * 4 + 1] = lds128(a + 1024);
            w[grp * 4 + 2] = lds128(a + 2048); w[grp * 4 + 3] = lds128(a + 3072);
            to_afrag(w[grp * 4], w[grp * 4 + 1], w[grp * 4 + 2], w[grp * 4 + 3]);
            advance();
        }
    }
    if (b < N_DOWN) {
        mbar_wait(bar_full + 8 * s, ph);
        const uint32_t a = sbase + SM_RING + s * TILE_BYTES + wf_off;
        w[32] = lds128(a); w[33] = lds128(a + 1024); w[34] = lds128(a + 2048); w[35] = lds128(a + 3072);
        to_afrag(w[32], w[33], w[34], w[35]);
        advance();
    } else {
        w[32] = w[33] = w[34] = w[35] = make_uint4(0, 0, 0, 0);
    }
    __syncwarp();
    {
        float4 sa = *reinterpret_cast<float4*>(p_s + lane * 8);
        float4 sb = *reinterpret_cast<float4*>(p_s + lane * 8 + 4);
        float m = fmaxf(fmaxf(fmaxf(sa.x, sa.y), fmaxf(sa.z, sa.w)), fmaxf(fmaxf(sb.x, sb.y), fmaxf(sb.z, sb.w)));
#pragma unroll
        for (int o = 16; o > 0; o >>= 1) m = fmaxf(m, __shfl_xor_sync(0xffffffffu, m, o));
        sa.x = exp2f(sa.x - m); sa.y = exp2f(sa.y - m); sa.z = exp2f(sa.z - m); sa.w = exp2f(sa.w - m);
        sb.x = exp2f(sb.x - m); sb.y = exp2f(sb.y - m); sb.z = exp2f(sb.z - m); sb.w = exp2f(sb.w - m);
        float l = ((sa.x + sa.y) + (sa.z + sa.w)) + ((sb.x + sb.y) + (sb.z + sb.w));
#pragma unroll
        for (int o = 16; o > 0; o >>= 1) l += __shfl_xor_sync(0xffffffffu, l, o);
        *reinterpret_cast<float4*>(p_s + lane * 8) = sa;
        *reinterpret_cast<float4*>(p_s + lane * 8 + 4) = sb;
        if (lane == 0) st_pkt(&g_stats[h * 32 + split * 8 + warp], m, l, tag);
        named_bar_arrive(BAR_KDONE, 288);
        __syncwarp();
    }
    float acc[8];
#pragma unroll
    for (int j = 0; j < 8; j++) acc[j] = 0.f;
    float c[2][4][4];
#pragma unroll
    for (int u = 0; u < 2; u++)
#pragma unroll
        for (int j = 0; j < 4; j++) c[u][j][0] = c[u][j][1] = c[u][j][2] = c[u][j][3] = 0.f;
    const uint32_t* bf = bfrag_s + g * 72 + 2 * t;
    float fw = 0.f;
    const float* p_rd = p_s + (lane >> 4) * 4;
#pragma unroll 1
    for (int it = 0; it < NT; it++) {
        const float4 p = *reinterpret_cast<const float4*>(p_rd + it * 8);
        if (it == NT - TAIL_LEAD) {
            st_pkt(&g_slots[((tid >> 1) * N_ATTN + b) * 2 + (tid & 1)], 0.f, 0.f, 0u);
            named_bar_sync(BAR_SCALE, 288);
            fw = fw_s[warp];
            const uint2 bb = *reinterpret_cast<const uint2*>(bf + 64);
            mma16816(c[0][0], w[32].x, w[33].x, w[34].x, w[35].x, bb.x, bb.y);
            mma16816(c[0][1], w[32].y, w[33].y, w[34].y, w[35].y, bb.x, bb.y);
            mma16816(c[0][2], w[32].z, w[33].z, w[34].z, w[35].z, bb.x, bb.y);
            mma16816(c[0][3], w[32].w, w[33].w, w[34].w, w[35].w, bb.x, bb.y);
        }
        mbar_wait(bar_full + 8 * s, ph);
        const uint32_t a = sbase + SM_RING + s * TILE_BYTES + my_off;
        const uint4 v0 = lds128(a), v1 = lds128(a + 512), v2 = lds128(a + 1024), v3 = lds128(a + 1536);
        axpy8(acc, p.x, v0);
        axpy8(acc, p.y, v1);
        axpy8(acc, p.z, v2);
        axpy8(acc, p.w, v3);
        advance();
    }
    {
        const bool up = lane >= 16;
        float o[4];
#pragma unroll
        for (int j = 0; j < 4; j++) {
            const float keep = up ? acc[4 + j] : acc[j], send = up ? acc[j] : acc[4 + j];
            o[j] = (keep + __shfl_xor_sync(0xffffffffu, send, 16)) * fw;
        }
        const __nv_bfloat162 w0 = __floats2bfloat162_rn(o[0], o[1]), w1 = __floats2bfloat162_rn(o[2], o[3]);
        *reinterpret_cast<uint2*>(bfrag_s + warp * 72 + (lane & 15) * 4 + (lane >> 4) * 2) =
            make_uint2(*reinterpret_cast<const uint32_t*>(&w0), *reinterpret_cast<const uint32_t*>(&w1));
    }
    named_bar_sync(BAR_CONS, NCW * 32);
    {
#pragma unroll
        for (int ks = 0; ks < 8; ks++) {
            const uint2 bb = *reinterpret_cast<const uint2*>(bf + 8 * ks);
            mma16816(c[ks & 1][0], w[ks * 4].x, w[ks * 4 + 1].x, w[ks * 4 + 2].x, w[ks * 4 + 3].x, bb.x, bb.y);
            mma16816(c[ks & 1][1], w[ks * 4].y, w[ks * 4 + 1].y, w[ks * 4 + 2].y, w[ks * 4 + 3].y, bb.x, bb.y);
            mma16816(c[ks & 1][2], w[ks * 4].z, w[ks * 4 + 1].z, w[ks * 4 + 2].z, w[ks * 4 + 3].z, bb.x, bb.y);
            mma16816(c[ks & 1][3], w[ks * 4].w, w[ks * 4 + 1].w, w[ks * 4 + 2].w, w[ks * 4 + 3].w, bb.x, bb.y);
        }
        float ya[4], yb[4];
#pragma unroll
        for (int j = 0; j < 4; j++) {
            ya[j] = (c[0][j][0] + c[1][j][0]) + (c[0][j][1] + c[1][j][1]);
            yb[j] = (c[0][j][2] + c[1][j][2]) + (c[0][j][3] + c[1][j][3]);
        }
        const bool t1 = t & 2, t0 = t & 1;
        const float a0 = (t1 ? ya[2] : ya[0]) + __shfl_xor_sync(0xffffffffu, t1 ? ya[0] : ya[2], 2);
        const float a1 = (t1 ? ya[3] : ya[1]) + __shfl_xor_sync(0xffffffffu, t1 ? ya[1] : ya[3], 2);
        const float b0 = (t1 ? yb[2] : yb[0]) + __shfl_xor_sync(0xffffffffu, t1 ? yb[0] : yb[2], 2);
        const float b1 = (t1 ? yb[3] : yb[1]) + __shfl_xor_sync(0xffffffffu, t1 ? yb[1] : yb[3], 2);
        const float y0 = (t0 ? a1 : a0) + __shfl_xor_sync(0xffffffffu, t0 ? a0 : a1, 1);
        const float y1 = (t0 ? b1 : b0) + __shfl_xor_sync(0xffffffffu, t0 ? b0 : b1, 1);
        st_pkt(&g_slots[((tid >> 1) * N_ATTN + b) * 2 + (tid & 1)], y0, y1, tag);
    }
    if (warp < 2) {
        const uint4* sp = &g_slots[(b * N_ATTN + lane) * 2 + warp];
        float a0, a1;
        unsigned n = 0;
        while (true) {
            uint64_t v[4][2];
#pragma unroll
            for (int k = 0; k < 4; k++)
                asm volatile("ld.relaxed.gpu.global.v2.b64 {%0, %1}, [%2];"
                             : "=l"(v[k][0]), "=l"(v[k][1]) : "l"(sp + 64 * k) : "memory");
            bool ok = true;
            a0 = a1 = 0.f;
#pragma unroll
            for (int k = 0; k < 4; k++) {
                ok = ok && (uint32_t)(v[k][0] >> 32) == tag && (uint32_t)(v[k][1] >> 32) == tag;
                a0 += __uint_as_float((uint32_t)v[k][0]);
                a1 += __uint_as_float((uint32_t)v[k][1]);
            }
            if (ok || ++n > SPIN_LIMIT) break;
        }
        __syncwarp();
#pragma unroll
        for (int o = 16; o > 0; o >>= 1) {
            a0 += __shfl_xor_sync(0xffffffffu, a0, o);
            a1 += __shfl_xor_sync(0xffffffffu, a1, o);
        }
        if (lane == 0) {
            *reinterpret_cast<__nv_bfloat162*>(out + 4 * b + 2 * warp) = __floats2bfloat162_rn(a0, a1);
            if (b == 0 && warp == 0) g_epoch = tag;
        }
    }
}

constexpr int FB_SPLIT = 16;
__device__ float fb_q[NH * DH];
__device__ float fb_h[FF];
__device__ float fb_part[NH * FB_SPLIT * (DH + 2)];
__device__ float fb_o[NH * DH];

__global__ void fb_proj_kernel(const __nv_bfloat16* x, const __nv_bfloat16* wq, const __nv_bfloat16* w_gate,
                               const __nv_bfloat16* w_up) {
    const int i = blockIdx.x * blockDim.x + threadIdx.x;
    if (i < NH * DH) {
        float a = 0.f;
        for (int d = 0; d < D_MODEL; d++) a = fmaf(__bfloat162float(x[d]), __bfloat162float(wq[(size_t)d * NH * DH + i]), a);
        fb_q[i] = a * 0.08838834764831845f;
    } else if (i < NH * DH + FF) {
        const int f = i - NH * DH;
        float gsum = 0.f, usum = 0.f;
        for (int d = 0; d < D_MODEL; d++) {
            const float xv = __bfloat162float(x[d]);
            gsum = fmaf(xv, __bfloat162float(w_gate[(size_t)d * FF + f]), gsum);
            usum = fmaf(xv, __bfloat162float(w_up[(size_t)d * FF + f]), usum);
        }
        fb_h[f] = gsum * usum;
    }
}
__global__ void fb_attn_kernel(const __nv_bfloat16* kc, const __nv_bfloat16* vc) {
    constexpr int NK = SK / FB_SPLIT;
    __shared__ float q_s[DH], p_s[NK], red[DH];
    const int h = blockIdx.x / FB_SPLIT, sp = blockIdx.x % FB_SPLIT, tid = threadIdx.x;
    const size_t base = ((size_t)h * SK + (size_t)sp * NK) * DH;
    q_s[tid] = fb_q[h * DH + tid];
    __syncthreads();
    float m = -INFINITY;
    for (int k = tid; k < NK; k += DH) {
        float a = 0.f;
        for (int d = 0; d < DH; d++) a = fmaf(q_s[d], __bfloat162float(kc[base + (size_t)k * DH + d]), a);
        p_s[k] = a;
        m = fmaxf(m, a);
    }
    red[tid] = m;
    __syncthreads();
    for (int i = 0; i < DH; i++) m = fmaxf(m, red[i]);
    __syncthreads();
    float l = 0.f;
    for (int k = tid; k < NK; k += DH) {
        p_s[k] = __expf(p_s[k] - m);
        l += p_s[k];
    }
    red[tid] = l;
    __syncthreads();
    float o = 0.f;
    for (int k = 0; k < NK; k++) o = fmaf(p_s[k], __bfloat162float(vc[base + (size_t)k * DH + tid]), o);
    float* dst = fb_part + (size_t)blockIdx.x * (DH + 2);
    dst[tid] = o;
    if (tid == 0) {
        l = 0.f;
        for (int i = 0; i < DH; i++) l += red[i];
        dst[DH] = m;
        dst[DH + 1] = l;
    }
}
__global__ void fb_combine_kernel() {
    const int h = blockIdx.x, tid = threadIdx.x;
    const float* src = fb_part + (size_t)h * FB_SPLIT * (DH + 2);
    float m = -INFINITY;
    for (int i = 0; i < FB_SPLIT; i++) m = fmaxf(m, src[i * (DH + 2) + DH]);
    float l = 0.f, o = 0.f;
    for (int i = 0; i < FB_SPLIT; i++) {
        const float e = __expf(src[i * (DH + 2) + DH] - m);
        l = fmaf(e, src[i * (DH + 2) + DH + 1], l);
        o = fmaf(e, src[i * (DH + 2) + tid], o);
    }
    fb_o[h * DH + tid] = o / l;
}
__global__ void fb_out_kernel(const __nv_bfloat16* x, const __nv_bfloat16* wo, const __nv_bfloat16* w_down,
                              const __nv_bfloat16* gate_w, __nv_bfloat16* out) {
    const int c = blockIdx.x * blockDim.x + threadIdx.x;
    float z = 0.f, a = 0.f, bsum = 0.f;
    for (int d = 0; d < D_MODEL; d++) z = fmaf(__bfloat162float(x[d]), __bfloat162float(gate_w[d]), z);
    for (int r = 0; r < NH * DH; r++) a = fmaf(fb_o[r], __bfloat162float(wo[(size_t)r * D_MODEL + c]), a);
    for (int f = 0; f < FF; f++) bsum = fmaf(fb_h[f], __bfloat162float(w_down[(size_t)f * D_MODEL + c]), bsum);
    const float gt = 1.0f / (1.0f + __expf(-z));
    out[c] = __float2bfloat16(gt * a + (1.0f - gt) * bsum);
}

}

extern "C" void kernel_launch(void* const* d_in, const int* in_sizes, int n_in, void* d_out, int out_size) {
    (void)in_sizes; (void)n_in; (void)out_size;
    const __nv_bfloat16* x      = (const __nv_bfloat16*)d_in[0];
    const __nv_bfloat16* kc     = (const __nv_bfloat16*)d_in[1];
    const __nv_bfloat16* vc     = (const __nv_bfloat16*)d_in[2];
    const __nv_bfloat16* wq     = (const __nv_bfloat16*)d_in[3];
    const __nv_bfloat16* wo     = (const __nv_bfloat16*)d_in[4];
    const __nv_bfloat16* w_gate = (const __nv_bfloat16*)d_in[6];
    const __nv_bfloat16* w_up   = (const __nv_bfloat16*)d_in[7];
    const __nv_bfloat16* w_down = (const __nv_bfloat16*)d_in[8];
    const __nv_bfloat16* gate_w = (const __nv_bfloat16*)d_in[9];

    __nv_bfloat16* out = (__nv_bfloat16*)d_out;

    int dev = 0, sms = 0, per_sm = 0;
    cudaGetDevice(&dev);
    cudaDeviceGetAttribute(&sms, cudaDevAttrMultiProcessorCount, dev);
    const bool attr_ok =
        cudaFuncSetAttribute(fused_decode_kernel, cudaFuncAttributeMaxDynamicSharedMemorySize, SM_TOTAL) == cudaSuccess;
    if (attr_ok) cudaOccupancyMaxActiveBlocksPerMultiprocessor(&per_sm, fused_decode_kernel, NLAUNCH, SM_TOTAL);
    if (attr_ok && per_sm >= 1 && sms * per_sm >= N_CTA) {
        fused_decode_kernel<<<N_CTA, NLAUNCH, SM_TOTAL>>>(x, kc, vc, wq, wo, w_gate, w_up, w_down, gate_w, out);
    } else {
        (void)cudaGetLastError();
        fb_proj_kernel<<<(NH * DH + FF + 127) / 128, 128>>>(x, wq, w_gate, w_up);
        fb_attn_kernel<<<NH * FB_SPLIT, DH>>>(kc, vc);
        fb_combine_kernel<<<NH, DH>>>();
        fb_out_kernel<<<D_MODEL / 64, 64>>>(x, wo, w_down, gate_w, out);
    }
}
```
